```python
import torch

def _softmax(x, axis=-1):
    return torch.softmax(x, dim=axis)
def _gelu(x):
    return torch.nn.functional.gelu(x, approximate="tanh")
def _silu(x):
    return torch.nn.functional.silu(x)
def _sigmoid(x):
    return torch.sigmoid(x)
def _layernorm(x, axis=-1, eps=1e-5):
    m = x.mean(dim=axis, keepdim=True)
    v = x.var(dim=axis, keepdim=True, unbiased=False)
    return (x - m) / torch.sqrt(v + eps)
def _scatter_add(tgt, idx, src, axis=0):
    return tgt.clone().index_add_(axis, idx, src)
def _segment_sum(src, seg, n):
    out = torch.zeros((n,) + src.shape[1:], dtype=src.dtype)
    return out.index_add_(0, seg, src)
def _pad(x, pw):
    flat = tuple(v for pair in reversed(pw) for v in pair)
    return torch.nn.functional.pad(x, flat)

kernel_name = 'standalone__global_local_windowed_global_tokens__prompt'

def setup_inputs():

    _w = (lambda a: (lambda t: t.to(torch.bfloat16) if t.is_floating_point() else t)(torch.as_tensor(a)))
    B, H, S, D = 1, 16, 2048, 256
    return {
        "q": _w((lambda *s: torch.randn(*s, dtype=torch.bfloat16) * 0.8)(B, H, S, D)),
        "k": _w((lambda *s: torch.randn(*s, dtype=torch.bfloat16) * 0.8)(B, H, S, D)),
        "v": _w((lambda *s: torch.randn(*s, dtype=torch.bfloat16) * 0.05)(B, H, S, D)),
        "window": 32,
        "n_global": 2,
    }

def reference(q, k, v, window, n_global):
    B, H, S, D = q.shape
    scale = D ** -0.5
    scores = torch.einsum("bhqd,bhkd->bhqk", q, k) * scale
    idx = torch.arange(S)
    dist = idx[:, None] - idx[None, :]
    local = (dist <= window) & (dist >= -window)
    is_global_q = (idx < n_global)[:, None]
    is_global_k = (idx < n_global)[None, :]
    mask = local | is_global_q | is_global_k
    scores = torch.where(mask[None, None], scores, -1e9)
    p = _softmax(scores, axis=-1)
    return torch.einsum("bhqk,bhkd->bhqd", p, v)
```

```cpp
#include <cuda_runtime.h>
#include <cuda_bf16.h>
#include <cuda.h>
#include <stdint.h>

namespace {

constexpr int kS = 2048, kD = 256, kH = 16;
constexpr int kThreads = 256;
constexpr int kMaxWin = 32;
constexpr int kMaxGlob = 8;
constexpr int kWindowPieces = 3;

constexpr uint32_t kSlotBytes = 32768, kPieceBytes = 16384;
constexpr uint32_t kOffKg = 6 * kSlotBytes;
constexpr uint32_t kOffVg = kOffKg + 4096;
constexpr uint32_t kOffBar = kOffVg + 4096;
constexpr uint32_t kBarFull = kOffBar;
constexpr uint32_t kBarG = kBarFull + 28 * 8;
constexpr uint32_t kBarEmpty = kBarG + 8;
constexpr uint32_t kBarO = kBarEmpty + 8 * 8;
constexpr int kNumBars = 28 + 1 + 8 + 8;
constexpr uint32_t kSmemBytes = kOffBar + kNumBars * 8 + 1024;

constexpr float kNegBig = -1.0e30f;
constexpr float kScaleLog2 = 0.0625f * 1.4426950408889634f;

struct Maps { CUtensorMap k, v, q, o, kg, vg; };

__device__ uint4 g_part[kH * 16 * 4 * 16 * 9];

__device__ __forceinline__ uint32_t smem_u32(const void* p) { return (uint32_t)__cvta_generic_to_shared(p); }
__device__ __forceinline__ void mbar_init(uint32_t b, uint32_t c) {
    asm volatile("mbarrier.init.shared::cta.b64 [%0], %1;" ::"r"(b), "r"(c) : "memory");
}
__device__ __forceinline__ void mbar_expect(uint32_t b, uint32_t bytes) {
    asm volatile("mbarrier.arrive.expect_tx.shared::cta.b64 _, [%0], %1;" ::"r"(b), "r"(bytes) : "memory");
}
__device__ __forceinline__ void mbar_arrive(uint32_t b) {
    asm volatile("mbarrier.arrive.shared::cta.b64 _, [%0];" ::"r"(b) : "memory");
}
__device__ __forceinline__ void mbar_wait(uint32_t b) {
    asm volatile(
        "{\n.reg .pred p, q;\n.reg .u32 n;\nmov.u32 n, 0;\n"
        "LW%=:\n"
        "mbarrier.try_wait.parity.shared::cta.b64 p, [%0], 0;\n"
        "@p bra LD%=;\n"
        "add.u32 n, n, 1;\n"
        "setp.lt.u32 q, n, 4000000;\n"
        "@q bra LW%=;\n"
        "LD%=:\n}\n" ::"r"(b) : "memory");
}
__device__ __forceinline__ void tma_load(uint32_t dst, const CUtensorMap* m, uint32_t bar, int row, int chunk,
                                         int head, uint64_t pol) {
    asm volatile(
        "cp.async.bulk.tensor.4d.shared::cluster.global.mbarrier::complete_tx::bytes.L2::cache_hint "
        "[%0], [%1, {%3,%4,%5,%6}], [%2], %7;" ::"r"(dst), "l"(m), "r"(bar), "r"(0), "r"(row), "r"(chunk),
        "r"(head), "l"(pol) : "memory");
}
__device__ __forceinline__ void tma_load_nohint(uint32_t dst, const CUtensorMap* m, uint32_t bar, int row,
                                                int chunk, int head) {
    asm volatile(
        "cp.async.bulk.tensor.4d.shared::cluster.global.mbarrier::complete_tx::bytes "
        "[%0], [%1, {%3,%4,%5,%6}], [%2];" ::"r"(dst), "l"(m), "r"(bar), "r"(0), "r"(row), "r"(chunk), "r"(head)
        : "memory");
}
__device__ __forceinline__ void tma_store(uint32_t src, const CUtensorMap* m, int row, int chunk, int head) {
    asm volatile("cp.async.bulk.tensor.4d.global.shared::cta.bulk_group [%1, {%2,%3,%4,%5}], [%0];" ::"r"(src),
                 "l"(m), "r"(0), "r"(row), "r"(chunk), "r"(head) : "memory");
}
__device__ __forceinline__ float ex2(float x) {
    float y;
    asm("ex2.approx.ftz.f32 %0, %1;" : "=f"(y) : "f"(x));
    return y;
}
__device__ __forceinline__ uint32_t pack_bf16(float lo, float hi) {
    uint32_t r;
    asm("cvt.rn.bf16x2.f32 %0, %1, %2;" : "=r"(r) : "f"(hi), "f"(lo));
    return r;
}
__device__ __forceinline__ uint64_t make_desc(uint32_t addr, uint32_t lbo, uint32_t sbo) {
    return (uint64_t)((addr & 0x3FFFF) >> 4) | ((uint64_t)(lbo >> 4) << 16) | ((uint64_t)(sbo >> 4) << 32) |
           (1ull << 62);
}
__device__ __forceinline__ void wg_fence() { asm volatile("wgmma.fence.sync.aligned;" ::: "memory"); }
__device__ __forceinline__ void wg_commit() { asm volatile("wgmma.commit_group.sync.aligned;" ::: "memory"); }
template <int N>
__device__ __forceinline__ void wg_wait() { asm volatile("wgmma.wait_group.sync.aligned %0;" ::"n"(N) : "memory"); }

#define F4(a, i) "+f"(a[i]), "+f"(a[i + 1]), "+f"(a[i + 2]), "+f"(a[i + 3])
#define F16(a, i) F4(a, i), F4(a, i + 4), F4(a, i + 8), F4(a, i + 12)

__device__ __forceinline__ void wgmma_ss_n64(float (&d)[32], uint64_t da, uint64_t db, int acc) {
    asm volatile(
        "{\n.reg .pred p;\nsetp.ne.b32 p, %34, 0;\n"
        "wgmma.mma_async.sync.aligned.m64n64k16.f32.bf16.bf16 "
        "{%0,%1,%2,%3,%4,%5,%6,%7,%8,%9,%10,%11,%12,%13,%14,%15,"
        "%16,%17,%18,%19,%20,%21,%22,%23,%24,%25,%26,%27,%28,%29,%30,%31}, %32, %33, p, 1, 1, 0, 0;\n}\n"
        : F16(d, 0), F16(d, 16) : "l"(da), "l"(db), "r"(acc));
}
__device__ __forceinline__ void wgmma_ss_n8(float (&d)[4], uint64_t da, uint64_t db, int acc) {
    asm volatile(
        "{\n.reg .pred p;\nsetp.ne.b32 p, %6, 0;\n"
        "wgmma.mma_async.sync.aligned.m64n8k16.f32.bf16.bf16 {%0,%1,%2,%3}, %4, %5, p, 1, 1, 0, 0;\n}\n"
        : F4(d, 0) : "l"(da), "l"(db), "r"(acc));
}
__device__ __forceinline__ void wgmma_rs_n128(float (&d)[64], uint32_t a0, uint32_t a1, uint32_t a2, uint32_t a3,
                                              uint64_t db, int acc) {
    asm volatile(
        "{\n.reg .pred p;\nsetp.ne.b32 p, %69, 0;\n"
        "wgmma.mma_async.sync.aligned.m64n128k16.f32.bf16.bf16 "
        "{%0,%1,%2,%3,%4,%5,%6,%7,%8,%9,%10,%11,%12,%13,%14,%15,"
        "%16,%17,%18,%19,%20,%21,%22,%23,%24,%25,%26,%27,%28,%29,%30,%31,"
        "%32,%33,%34,%35,%36,%37,%38,%39,%40,%41,%42,%43,%44,%45,%46,%47,"
        "%48,%49,%50,%51,%52,%53,%54,%55,%56,%57,%58,%59,%60,%61,%62,%63}, "
        "{%64,%65,%66,%67}, %68, p, 1, 1, 1;\n}\n"
        : F16(d, 0), F16(d, 16), F16(d, 32), F16(d, 48)
        : "r"(a0), "r"(a1), "r"(a2), "r"(a3), "l"(db), "r"(acc));
}
__device__ __forceinline__ void mma_16816(float (&d)[4], uint32_t a0, uint32_t a1, uint32_t a2, uint32_t a3,
                                          uint32_t b0, uint32_t b1) {
    asm volatile(
        "mma.sync.aligned.m16n8k16.row.col.f32.bf16.bf16.f32 {%0,%1,%2,%3}, {%4,%5,%6,%7}, {%8,%9}, {%0,%1,%2,%3};"
        : F4(d, 0) : "r"(a0), "r"(a1), "r"(a2), "r"(a3), "r"(b0), "r"(b1));
}
__device__ __forceinline__ void ldsm_x4(uint32_t (&r)[4], uint32_t addr) {
    asm volatile("ldmatrix.sync.aligned.m8n8.x4.shared.b16 {%0,%1,%2,%3}, [%4];"
                 : "=r"(r[0]), "=r"(r[1]), "=r"(r[2]), "=r"(r[3]) : "r"(addr) : "memory");
}
__device__ __forceinline__ void ldsm_x4_t(uint32_t (&r)[4], uint32_t addr) {
    asm volatile("ldmatrix.sync.aligned.m8n8.x4.trans.shared.b16 {%0,%1,%2,%3}, [%4];"
                 : "=r"(r[0]), "=r"(r[1]), "=r"(r[2]), "=r"(r[3]) : "r"(addr) : "memory");
}
__device__ __forceinline__ void stsm_x4(uint32_t addr, uint32_t r0, uint32_t r1, uint32_t r2, uint32_t r3) {
    asm volatile("stmatrix.sync.aligned.m8n8.x4.shared.b16 [%0], {%1,%2,%3,%4};" ::"r"(addr), "r"(r0), "r"(r1),
                 "r"(r2), "r"(r3) : "memory");
}
__device__ __forceinline__ uint32_t movm_t(uint32_t a) {
    uint32_t d;
    asm volatile("movmatrix.sync.aligned.m8n8.trans.b16 %0, %1;" : "=r"(d) : "r"(a));
    return d;
}
__device__ __forceinline__ uint32_t enc(float f) {
    uint32_t u = ~__float_as_uint(f);
    return u ? u : 0x80000000u;
}
__device__ __forceinline__ float dec(uint32_t u) { return __uint_as_float(~u); }
__device__ __forceinline__ void st_part(uint4* p, float a, float b, float c, float d) {
    asm volatile("st.relaxed.gpu.global.v4.u32 [%0], {%1,%2,%3,%4};" ::"l"(p), "r"(enc(a)), "r"(enc(b)),
                 "r"(enc(c)), "r"(enc(d)) : "memory");
}
__device__ __forceinline__ uint4 ld_part(const uint4* p) {
    uint4 v;
    asm volatile("ld.relaxed.gpu.global.v4.u32 {%0,%1,%2,%3}, [%4];"
                 : "=r"(v.x), "=r"(v.y), "=r"(v.z), "=r"(v.w) : "l"(p) : "memory");
    return v;
}
__device__ __forceinline__ bool ready(const uint4& v) { return v.x && v.y && v.z && v.w; }

__device__ __noinline__ void generic_rows(const __nv_bfloat16* q, const __nv_bfloat16* k, const __nv_bfloat16* v,
                                          __nv_bfloat16* out, int head, int r0, int W, int G) {
    const int warp = threadIdx.x >> 5, lane = threadIdx.x & 31;
    const size_t hb = (size_t)head * kS * kD;
    for (int i = r0 + warp; i < r0 + 256; i += kThreads / 32) {
        float qf[8], o[8];
        {
            uint4 u = *reinterpret_cast<const uint4*>(q + hb + (size_t)i * kD + lane * 8);
            const __nv_bfloat16* e = reinterpret_cast<const __nv_bfloat16*>(&u);
#pragma unroll
            for (int x = 0; x < 8; x++) { qf[x] = __bfloat162float(e[x]); o[x] = 0.f; }
        }
        const bool none = (W < 0) && (G <= 0);
        float m = -INFINITY, l = 0.f;
#pragma unroll 1
        for (int j = 0; j < kS; j++) {
            const long long dist = (long long)i - j;
            const bool on = (dist <= W && dist >= -(long long)W) || i < G || j < G;
            if (!on && !none) continue;
            float s = -1.0e9f;
            if (on) {
                uint4 u = *reinterpret_cast<const uint4*>(k + hb + (size_t)j * kD + lane * 8);
                const __nv_bfloat16* e = reinterpret_cast<const __nv_bfloat16*>(&u);
                s = 0.f;
#pragma unroll
                for (int x = 0; x < 8; x++) s += qf[x] * __bfloat162float(e[x]);
#pragma unroll
                for (int x = 16; x; x >>= 1) s += __shfl_xor_sync(0xffffffffu, s, x);
                s *= 0.0625f;
            }
            const float mn = fmaxf(m, s);
            const float a = __expf(m - mn), p = __expf(s - mn);
            uint4 u = *reinterpret_cast<const uint4*>(v + hb + (size_t)j * kD + lane * 8);
            const __nv_bfloat16* e = reinterpret_cast<const __nv_bfloat16*>(&u);
#pragma unroll
            for (int x = 0; x < 8; x++) o[x] = o[x] * a + p * __bfloat162float(e[x]);
            l = l * a + p;
            m = mn;
        }
        const float inv = 1.f / l;
        uint4 r;
        r.x = pack_bf16(o[0] * inv, o[1] * inv);
        r.y = pack_bf16(o[2] * inv, o[3] * inv);
        r.z = pack_bf16(o[4] * inv, o[5] * inv);
        r.w = pack_bf16(o[6] * inv, o[7] * inv);
        *reinterpret_cast<uint4*>(out + hb + (size_t)i * kD + lane * 8) = r;
    }
}

template <bool FIRST>
__device__ __forceinline__ void local_half(uint32_t base, int blkK, int blkQ, int qrow, int krow, int W, int G,
                                           int warp, int lane, bool release, float (&o0)[64], float (&o1)[64],
                                           float& m0, float& m1, float& l0, float& l1) {
    const uint32_t sK = base + (uint32_t)(blkK % 6) * kSlotBytes;
    const uint32_t sV = sK + kSlotBytes;
    const uint32_t sQ = base + (uint32_t)(blkQ % 6) * kSlotBytes;
    const uint32_t fK = base + kBarFull + blkK * 16, fV = fK + 16, fQ = base + kBarFull + blkQ * 16;
    float s[32], sg[4];
    const uint64_t dQ = make_desc(sQ, 16, 1024), dK = make_desc(sK, 16, 1024);
    const uint64_t dKg = make_desc(base + kOffKg, 16, 1024);
#pragma unroll
    for (int p = 0; p < 2; p++) {
        if (FIRST) mbar_wait(fQ + 8 * p); else mbar_wait(fK + 8 * p);
        wg_fence();
#pragma unroll
        for (int x = 0; x < 8; x++) {
            const int kk = p * 8 + x;
            const uint32_t off = ((kk >> 2) * 8192 + (kk & 3) * 32) >> 4;
            wgmma_ss_n64(s, dQ + off, dK + off, kk);
            if (FIRST) wgmma_ss_n8(sg, dQ + off, dKg + (((kk >> 2) * 1024 + (kk & 3) * 32) >> 4), kk);
        }
    }
    wg_commit();
    const int i0 = qrow + warp * 16 + (lane >> 2), cq = krow + 2 * (lane & 3);
    const int lo0 = max(i0 - W, G) - cq, hi0 = min(i0 + W, kS - 1) - cq;
    const int lo1 = max(i0 + 8 - W, G) - cq, hi1 = min(i0 + 8 + W, kS - 1) - cq;
    wg_wait<0>();
    if (FIRST && release && lane == 0) mbar_arrive(base + kBarEmpty + blkK * 8);

    float mx0, mx1;
    if (FIRST) {
        const int g0 = 2 * (lane & 3);
        sg[0] = g0 < G ? sg[0] : kNegBig;
        sg[1] = g0 + 1 < G ? sg[1] : kNegBig;
        sg[2] = g0 < G ? sg[2] : kNegBig;
        sg[3] = g0 + 1 < G ? sg[3] : kNegBig;
        mx0 = fmaxf(sg[0], sg[1]);
        mx1 = fmaxf(sg[2], sg[3]);
    } else {
        mx0 = m0;
        mx1 = m1;
    }
#pragma unroll
    for (int j = 0; j < 8; j++) {
#pragma unroll
        for (int e = 0; e < 2; e++) {
            const int c = 8 * j + e;
            s[4 * j + e] = (c >= lo0 && c <= hi0) ? s[4 * j + e] : kNegBig;
            s[4 * j + 2 + e] = (c >= lo1 && c <= hi1) ? s[4 * j + 2 + e] : kNegBig;
            mx0 = fmaxf(mx0, s[4 * j + e]);
            mx1 = fmaxf(mx1, s[4 * j + 2 + e]);
        }
    }
    mx0 = fmaxf(mx0, __shfl_xor_sync(0xffffffffu, mx0, 1));
    mx1 = fmaxf(mx1, __shfl_xor_sync(0xffffffffu, mx1, 1));
    mx0 = fmaxf(mx0, __shfl_xor_sync(0xffffffffu, mx0, 2));
    mx1 = fmaxf(mx1, __shfl_xor_sync(0xffffffffu, mx1, 2));
    const float b0 = -mx0 * kScaleLog2, b1 = -mx1 * kScaleLog2;
    uint32_t pg0 = 0, pg1 = 0;
    if (FIRST) {
        sg[0] = ex2(fmaf(sg[0], kScaleLog2, b0));
        sg[1] = ex2(fmaf(sg[1], kScaleLog2, b0));
        sg[2] = ex2(fmaf(sg[2], kScaleLog2, b1));
        sg[3] = ex2(fmaf(sg[3], kScaleLog2, b1));
        l0 = sg[0] + sg[1];
        l1 = sg[2] + sg[3];
        pg0 = pack_bf16(sg[0], sg[1]);
        pg1 = pack_bf16(sg[2], sg[3]);
    } else {
        const float a0 = ex2(fmaf(m0, kScaleLog2, b0)), a1 = ex2(fmaf(m1, kScaleLog2, b1));
        l0 *= a0;
        l1 *= a1;
#pragma unroll
        for (int j = 0; j < 16; j++) {
            o0[4 * j] *= a0; o0[4 * j + 1] *= a0; o0[4 * j + 2] *= a1; o0[4 * j + 3] *= a1;
            o1[4 * j] *= a0; o1[4 * j + 1] *= a0; o1[4 * j + 2] *= a1; o1[4 * j + 3] *= a1;
        }
    }
    m0 = mx0;
    m1 = mx1;
    uint32_t pa[16];
#pragma unroll
    for (int j = 0; j < 8; j++) {
        const float p0 = ex2(fmaf(s[4 * j], kScaleLog2, b0)), p1 = ex2(fmaf(s[4 * j + 1], kScaleLog2, b0));
        const float p2 = ex2(fmaf(s[4 * j + 2], kScaleLog2, b1)), p3 = ex2(fmaf(s[4 * j + 3], kScaleLog2, b1));
        l0 += p0 + p1;
        l1 += p2 + p3;
        pa[2 * j] = pack_bf16(p0, p1);
        pa[2 * j + 1] = pack_bf16(p2, p3);
    }
    const uint64_t dV = make_desc(sV, 8192, 1024);
    const uint64_t dVg = make_desc(base + kOffVg, 1024, 0);
    if (!FIRST) mbar_wait(fV);
    wg_fence();
    if (FIRST) wgmma_rs_n128(o0, pg0, pg1, 0u, 0u, dVg, 0);
#pragma unroll
    for (int kk = 0; kk < 4; kk++)
        wgmma_rs_n128(o0, pa[4 * kk], pa[4 * kk + 1], pa[4 * kk + 2], pa[4 * kk + 3], dV + ((kk * 2048) >> 4), 1);
    wg_commit();
    if (!FIRST) { mbar_wait(fV + 8); wg_fence(); }
    if (FIRST) wgmma_rs_n128(o1, pg0, pg1, 0u, 0u, dVg + (2048 >> 4), 0);
#pragma unroll
    for (int kk = 0; kk < 4; kk++)
        wgmma_rs_n128(o1, pa[4 * kk], pa[4 * kk + 1], pa[4 * kk + 2], pa[4 * kk + 3],
                      dV + ((kPieceBytes + kk * 2048) >> 4), 1);
    wg_commit();
    if (FIRST) {
        wg_wait<0>();
        if (release && lane == 0) mbar_arrive(base + kBarEmpty + (blkK + 1) * 8);
    }
}

__device__ __forceinline__ void stage_piece(uint32_t dst, uint32_t bar, const float (&o)[64], float r0, float r1,
                                            int lane) {
#pragma unroll
    for (int x = 0; x < 8; x++) {
        const uint32_t addr = dst + (x >> 2) * 8192 + ((((x & 3) * 2 + (lane >> 4)) ^ (lane & 7)) << 4);
        stsm_x4(addr, pack_bf16(o[8 * x] * r0, o[8 * x + 1] * r0), pack_bf16(o[8 * x + 2] * r1, o[8 * x + 3] * r1),
                pack_bf16(o[8 * x + 4] * r0, o[8 * x + 5] * r0), pack_bf16(o[8 * x + 6] * r1, o[8 * x + 7] * r1));
    }
    asm volatile("fence.proxy.async.shared::cta;" ::: "memory");
    __syncwarp();
    if (lane == 0) mbar_arrive(bar);
}

__global__ void __launch_bounds__(kThreads, 1)
attn_kernel(const __grid_constant__ Maps maps, const __nv_bfloat16* __restrict__ q,
            const __nv_bfloat16* __restrict__ k, const __nv_bfloat16* __restrict__ v,
            __nv_bfloat16* __restrict__ out, const int* __restrict__ p_win, const int* __restrict__ p_glob) {
    extern __shared__ uint8_t smem_raw[];
    uint32_t base = (smem_u32(smem_raw) + 1023u) & ~1023u;
    asm volatile("" : "+r"(base));
    const int warp = __shfl_sync(0xffffffffu, threadIdx.x >> 5, 0), lane = threadIdx.x & 31;
    const int head = blockIdx.x >> 3, chunk = blockIdx.x & 7;
    const int r0 = chunk * 256;
    const bool bwd = chunk & 1;
    const int rq = bwd ? r0 + 192 : r0, rk = bwd ? r0 + 224 : r0 - 32, dr = bwd ? -64 : 64;

    uint64_t pol = 0;
    if (warp == 6) {
        if (lane == 0) {
            asm volatile("createpolicy.fractional.L2::evict_first.b64 %0, 1.0;" : "=l"(pol));
#pragma unroll
            for (int pc = 0; pc < kWindowPieces; pc++) {
                const uint32_t fb = base + kBarFull + 8 * pc;
                mbar_init(fb, 1);
                mbar_expect(fb, kPieceBytes);
                tma_load(base + pc * kPieceBytes, &maps.k + (pc >> 1), fb, (pc >> 1) == 2 ? rq : rk, 2 * (pc & 1),
                         head, pol);
            }
            mbar_init(base + kBarG, 1);
            mbar_expect(base + kBarG, 8192);
            tma_load_nohint(base + kOffKg, &maps.kg, base + kBarG, 0, 0, head);
            tma_load_nohint(base + kOffVg, &maps.vg, base + kBarG, 0, 0, head);
        }
    } else if (lane == 0) {
        const int w = warp == 7 ? 6 : warp;
#pragma unroll 1
        for (int b = kWindowPieces + w; b < kNumBars; b += 7) {
            if (b == 28) continue;
            uint32_t cnt = 1;
            if (b > 36) cnt = 4;
            else if (b > 28) cnt = ((b - 29) % 3 == 2) ? 1 : 6;
            mbar_init(base + kBarFull + 8 * b, cnt);
        }
    }
    const int W = __ldg(p_win), G = __ldg(p_glob);
    asm volatile("fence.mbarrier_init.release.cluster;" ::: "memory");
    __syncthreads();

    if (W < 0 || W > kMaxWin || G < 0 || G > kMaxGlob) {
        for (int pc = 0; pc < kWindowPieces; pc++) mbar_wait(base + kBarFull + 8 * pc);
        mbar_wait(base + kBarG);
        generic_rows(q, k, v, out, head, r0, W, G);
        return;
    }

    if (warp < 4) {
        float o0[64], o1[64];
        mbar_wait(base + kBarG);
        mbar_wait(base + kBarFull);
        mbar_wait(base + kBarFull + 8);
        mbar_wait(base + kBarFull + 16);
        mbar_wait(base + kBarFull + 24);
#pragma unroll 1
        for (int t = 0; t < 4; t++) {
            float m0, m1, l0, l1;
            const int qrow = rq + dr * t, krow = rk + dr * t;
            local_half<true>(base, 3 * t, 3 * t + 2, qrow, krow, W, G, warp, lane, t < 3, o0, o1, m0, m1, l0, l1);
            local_half<false>(base, 3 * t + 3, 3 * t + 2, qrow, krow + dr, W, G, warp, lane, false, o0, o1, m0, m1,
                              l0, l1);
            l0 += __shfl_xor_sync(0xffffffffu, l0, 1);
            l1 += __shfl_xor_sync(0xffffffffu, l1, 1);
            l0 += __shfl_xor_sync(0xffffffffu, l0, 2);
            l1 += __shfl_xor_sync(0xffffffffu, l1, 2);
            const float i0 = __fdividef(1.f, l0), i1 = __fdividef(1.f, l1);
            const uint32_t dst = base + (uint32_t)((3 * t + 2) % 6) * kSlotBytes + (warp * 16 + (lane & 15)) * 128;
            wg_wait<1>();
            stage_piece(dst, base + kBarO + 16 * t, o0, i0, i1, lane);
            wg_wait<0>();
            stage_piece(dst + kPieceBytes, base + kBarO + 16 * t + 8, o1, i0, i1, lane);
        }
    } else if (warp < 6) {
        const int g = warp - 4;
        uint32_t qb[32];
        {
            const uint32_t* qg =
                reinterpret_cast<const uint32_t*>(q + ((size_t)head * kS + (lane >> 2)) * kD) + (lane & 3);
#pragma unroll
            for (int x = 0; x < 32; x++) qb[x] = __ldg(qg + 4 * x);
        }
        float og[16][4];
#pragma unroll
        for (int i = 0; i < 16; i++) og[i][0] = og[i][1] = og[i][2] = og[i][3] = 0.f;
        float m0 = kNegBig, m1 = kNegBig, l0 = 0.f, l1 = 0.f;
        const bool pub = 2 * (lane & 3) < G;
        uint4* const rec = g_part + ((size_t)(head * 16 * 4 + (lane & 3)) * 16 + chunk * 2 + g) * 9;
#pragma unroll 1
        for (int u = 0; u < 8; u++) {
            const int j = (u + 1) >> 1;
            int row = 32 * g + 16 * ((u + 1) & 1);
            if (u == 0) row = (bwd ? 0 : 32) + 16 * g;
            if (u == 7) row = (bwd ? 32 : 0) + 16 * g;
            const uint32_t sK = base + (uint32_t)((3 * j) % 6) * kSlotBytes, sV = sK + kSlotBytes;
            const uint32_t fK = base + kBarFull + 48 * j;
            float sa[4][4];
#pragma unroll
            for (int c = 0; c < 4; c++) sa[c][0] = sa[c][1] = sa[c][2] = sa[c][3] = 0.f;
            const uint32_t aK = sK + (row + (lane & 15)) * 128;
#pragma unroll
            for (int c = 0; c < 4; c++) {
                if ((c & 1) == 0) mbar_wait(fK + 4 * c);
#pragma unroll
                for (int x = 0; x < 4; x++) {
                    uint32_t a[4];
                    ldsm_x4(a, aK + c * 8192 + (((2 * x + (lane >> 4)) ^ (lane & 7)) << 4));
                    mma_16816(sa[x], a[0], a[1], a[2], a[3], qb[8 * c + 2 * x], qb[8 * c + 2 * x + 1]);
                }
            }
            const bool last_of_block = (u & 1) == 0 && u < 6;
            __syncwarp();
            if (last_of_block && lane == 0) mbar_arrive(base + kBarEmpty + 24 * j);
            const float s0 = (sa[0][0] + sa[1][0]) + (sa[2][0] + sa[3][0]);
            const float s1 = (sa[0][1] + sa[1][1]) + (sa[2][1] + sa[3][1]);
            const float s2 = (sa[0][2] + sa[1][2]) + (sa[2][2] + sa[3][2]);
            const float s3 = (sa[0][3] + sa[1][3]) + (sa[2][3] + sa[3][3]);
            float mx0 = fmaxf(s0, s2), mx1 = fmaxf(s1, s3);
#pragma unroll
            for (int x = 4; x < 32; x <<= 1) {
                mx0 = fmaxf(mx0, __shfl_xor_sync(0xffffffffu, mx0, x));
                mx1 = fmaxf(mx1, __shfl_xor_sync(0xffffffffu, mx1, x));
            }
            mx0 = fmaxf(mx0, m0);
            mx1 = fmaxf(mx1, m1);
            const float b0 = -mx0 * kScaleLog2, b1 = -mx1 * kScaleLog2;
            const float a0 = ex2(fmaf(m0, kScaleLog2, b0)), a1 = ex2(fmaf(m1, kScaleLog2, b1));
            const float p0 = ex2(fmaf(s0, kScaleLog2, b0)), p1 = ex2(fmaf(s1, kScaleLog2, b1));
            const float p2 = ex2(fmaf(s2, kScaleLog2, b0)), p3 = ex2(fmaf(s3, kScaleLog2, b1));
            m0 = mx0;
            m1 = mx1;
            l0 = l0 * a0 + (p0 + p2);
            l1 = l1 * a1 + (p1 + p3);
            const uint32_t pb0 = movm_t(pack_bf16(p0, p1)), pb1 = movm_t(pack_bf16(p2, p3));
#pragma unroll
            for (int i = 0; i < 16; i++) { og[i][0] *= a0; og[i][1] *= a1; og[i][2] *= a0; og[i][3] *= a1; }
            if (u == 7) {
#pragma unroll
                for (int x = 4; x < 32; x <<= 1) {
                    l0 += __shfl_xor_sync(0xffffffffu, l0, x);
                    l1 += __shfl_xor_sync(0xffffffffu, l1, x);
                }
                if (pub) {
                    st_part(rec + (size_t)(lane >> 2) * (4 * 16 * 9) + 8, m0, m1, l0, l1);
                    st_part(rec + (size_t)((lane >> 2) + 8) * (4 * 16 * 9) + 8, m0, m1, l0, l1);
                }
            }
            const uint32_t aV = sV + (row + (lane & 7) + ((lane >> 4) << 3)) * 128;
#pragma unroll
            for (int c = 0; c < 4; c++) {
                if ((c & 1) == 0) mbar_wait(fK + 16 + 4 * c);
#pragma unroll
                for (int x = 0; x < 4; x++) {
                    uint32_t a[4];
                    ldsm_x4_t(a, aV + c * 8192 + (((2 * x + ((lane >> 3) & 1)) ^ (lane & 7)) << 4));
                    mma_16816(og[4 * c + x], a[0], a[1], a[2], a[3], pb0, pb1);
                }
            }
            __syncwarp();
            if (last_of_block && lane == 0) mbar_arrive(base + kBarEmpty + 24 * j + 8);
        }
        if (pub) {
#pragma unroll
            for (int i = 0; i < 16; i++)
                st_part(rec + (size_t)i * (4 * 16 * 9) + (lane >> 2), og[i][0], og[i][1], og[i][2], og[i][3]);
        }
        const int mt = chunk * 2 + g;
#pragma unroll 1
        for (int qp = 0; 2 * qp < G; qp++) {
            uint4* const in = g_part + ((size_t)((head * 16 + mt) * 4 + qp) * 16 + (lane >> 3) * 4) * 9;
            uint4 ml[4], ov[4];
            int it = 0;
            bool ok;
            do {
#pragma unroll
                for (int x = 0; x < 4; x++) ml[x] = ld_part(in + x * 9 + 8);
                ok = ready(ml[0]) && ready(ml[1]) && ready(ml[2]) && ready(ml[3]);
            } while (!ok && ++it < 2000000);
            __syncwarp();
            float M0 = fmaxf(fmaxf(dec(ml[0].x), dec(ml[1].x)), fmaxf(dec(ml[2].x), dec(ml[3].x)));
            float M1 = fmaxf(fmaxf(dec(ml[0].y), dec(ml[1].y)), fmaxf(dec(ml[2].y), dec(ml[3].y)));
#pragma unroll
            for (int x = 8; x < 32; x <<= 1) {
                M0 = fmaxf(M0, __shfl_xor_sync(0xffffffffu, M0, x));
                M1 = fmaxf(M1, __shfl_xor_sync(0xffffffffu, M1, x));
            }
            float w0[4], w1[4], L0 = 0.f, L1 = 0.f;
#pragma unroll
            for (int x = 0; x < 4; x++) {
                w0[x] = ex2((dec(ml[x].x) - M0) * kScaleLog2);
                w1[x] = ex2((dec(ml[x].y) - M1) * kScaleLog2);
                L0 += w0[x] * dec(ml[x].z);
                L1 += w1[x] * dec(ml[x].w);
            }
#pragma unroll
            for (int x = 8; x < 32; x <<= 1) {
                L0 += __shfl_xor_sync(0xffffffffu, L0, x);
                L1 += __shfl_xor_sync(0xffffffffu, L1, x);
            }
            const float i0 = __fdividef(1.f, L0), i1 = __fdividef(1.f, L1);
            it = 0;
            do {
#pragma unroll
                for (int x = 0; x < 4; x++) ov[x] = ld_part(in + x * 9 + (lane & 7));
                ok = ready(ov[0]) && ready(ov[1]) && ready(ov[2]) && ready(ov[3]);
            } while (!ok && ++it < 2000000);
            __syncwarp();
            float c0 = 0.f, c1 = 0.f, c2 = 0.f, c3 = 0.f;
#pragma unroll
            for (int x = 0; x < 4; x++) {
                c0 += w0[x] * dec(ov[x].x);
                c1 += w1[x] * dec(ov[x].y);
                c2 += w0[x] * dec(ov[x].z);
                c3 += w1[x] * dec(ov[x].w);
            }
#pragma unroll
            for (int x = 8; x < 32; x <<= 1) {
                c0 += __shfl_xor_sync(0xffffffffu, c0, x);
                c1 += __shfl_xor_sync(0xffffffffu, c1, x);
                c2 += __shfl_xor_sync(0xffffffffu, c2, x);
                c3 += __shfl_xor_sync(0xffffffffu, c3, x);
            }
            const int sel = lane >> 3;
            const float val = sel == 0 ? c0 * i0 : sel == 1 ? c1 * i1 : sel == 2 ? c2 * i0 : c3 * i1;
            const int orow = 2 * qp + (sel & 1);
            if (orow < G)
                out[((size_t)head * kS + orow) * kD + 16 * mt + (lane & 7) + 8 * (sel >> 1)] = __float2bfloat16(val);
#pragma unroll
            for (int x = 0; x < 4; x++) in[x * 9 + (lane & 7)] = make_uint4(0, 0, 0, 0);
            if ((lane & 7) < 4) in[(lane & 7) * 9 + 8] = make_uint4(0, 0, 0, 0);
        }
    } else if (warp == 6) {
        if (lane == 0) {
            int blk = kWindowPieces >> 1, ty = blk % 3, idx = blk / 3;
#pragma unroll 1
            for (int pc = kWindowPieces; pc < 28; pc++) {
                const int h = pc & 1;
                if (h == 0 && blk >= 6) mbar_wait(base + kBarEmpty + 8 * (blk - 6));
                mbar_wait(base + kBarFull + 8 * (pc - kWindowPieces));
                const uint32_t fb = base + kBarFull + 8 * pc;
                mbar_expect(fb, kPieceBytes);
                tma_load(base + (uint32_t)((idx & 1) * 3 + ty) * kSlotBytes + h * kPieceBytes, &maps.k + ty, fb,
                         (ty == 2 ? rq : rk) + dr * idx, 2 * h, head, pol);
                if (h) {
                    blk++;
                    if (++ty == 3) { ty = 0; idx++; }
                }
            }
        }
    } else {
        if (lane == 0) {
#pragma unroll 1
            for (int t = 0; t < 4; t++) {
                const uint32_t src = base + (uint32_t)((t & 1) * 3 + 2) * kSlotBytes;
                mbar_wait(base + kBarO + 16 * t);
                tma_store(src, &maps.o, rq + dr * t, 0, head);
                mbar_wait(base + kBarO + 16 * t + 8);
                tma_store(src + kPieceBytes, &maps.o, rq + dr * t, 2, head);
                asm volatile("cp.async.bulk.commit_group;" ::: "memory");
                if (t == 0) asm volatile("cp.async.bulk.wait_group 0;" ::: "memory");
                else asm volatile("cp.async.bulk.wait_group.read 0;" ::: "memory");
                if (t < 2) mbar_arrive(base + kBarEmpty + 8 * (3 * t + 2));
            }
        }
    }
}

typedef CUresult (*EncodeTiledFn)(CUtensorMap*, CUtensorMapDataType, cuuint32_t, void*, const cuuint64_t*,
                                  const cuuint64_t*, const cuuint32_t*, const cuuint32_t*, CUtensorMapInterleave,
                                  CUtensorMapSwizzle, CUtensorMapL2promotion, CUtensorMapFloatOOBfill);

void encode(EncodeTiledFn fn, CUtensorMap* m, const void* ptr, uint32_t rows, uint32_t chunks) {
    cuuint64_t dims[4] = {64, (cuuint64_t)kS, 4, (cuuint64_t)kH};
    cuuint64_t strides[3] = {(cuuint64_t)kD * 2, 128, (cuuint64_t)kS * kD * 2};
    cuuint32_t box[4] = {64, rows, chunks, 1};
    cuuint32_t es[4] = {1, 1, 1, 1};
    fn(m, CU_TENSOR_MAP_DATA_TYPE_BFLOAT16, 4, const_cast<void*>(ptr), dims, strides, box, es,
       CU_TENSOR_MAP_INTERLEAVE_NONE, CU_TENSOR_MAP_SWIZZLE_128B, CU_TENSOR_MAP_L2_PROMOTION_NONE,
       CU_TENSOR_MAP_FLOAT_OOB_FILL_NONE);
}

}

extern "C" void kernel_launch(void* const* d_in, const int* in_sizes, int n_in, void* d_out, int out_size) {
    (void)in_sizes; (void)n_in; (void)out_size;
    const __nv_bfloat16* q = (const __nv_bfloat16*)d_in[0];
    const __nv_bfloat16* k = (const __nv_bfloat16*)d_in[1];
    const __nv_bfloat16* v = (const __nv_bfloat16*)d_in[2];
    const int* win = (const int*)d_in[3];
    const int* glob = (const int*)d_in[4];
    __nv_bfloat16* out = (__nv_bfloat16*)d_out;

    void* fn = nullptr;
    cudaDriverEntryPointQueryResult qr;
    cudaGetDriverEntryPoint("cuTensorMapEncodeTiled", &fn, cudaEnableDefault, &qr);
    EncodeTiledFn enc_fn = (EncodeTiledFn)fn;
    Maps maps;
    encode(enc_fn, &maps.k, k, 64, 2);
    encode(enc_fn, &maps.v, v, 64, 2);
    encode(enc_fn, &maps.q, q, 64, 2);
    encode(enc_fn, &maps.o, out, 64, 2);
    encode(enc_fn, &maps.kg, k, 8, 4);
    encode(enc_fn, &maps.vg, v, 8, 4);
    cudaFuncSetAttribute(attn_kernel, cudaFuncAttributeMaxDynamicSharedMemorySize, kSmemBytes);
    attn_kernel<<<kH * 8, kThreads, kSmemBytes>>>(maps, q, k, v, out, win, glob);
}
```

```cpp
#include <cuda_runtime.h>
#include <cuda_bf16.h>
#include <cuda.h>
#include <stdint.h>

namespace {

constexpr int kS = 2048, kD = 256, kH = 16;
constexpr int kThreads = 384;
constexpr int kMaxWin = 32;
constexpr int kMaxGlob = 8;
#define WINP 5
#define BURST 8
constexpr int kWindowPieces = WINP;
constexpr int kBurstPieces = BURST;
#define PACE 345
#define PACE0 -550
#define FREEP 10
constexpr int kPace = PACE, kPace0 = PACE0, kFreePieces = FREEP;

constexpr unsigned long long kBlkType = 0x22012102102101ull;
constexpr unsigned long long kBlkIdx  = 0x33342321210100ull;
constexpr unsigned long long kBlkSlot = 0x55035425315403ull;
constexpr unsigned long long kBlkWait = 0xF67251F40FFFFFull;
#define LASTMODE 1
#define POLLSLEEP 0
#define TUNE_PARAM
#define TUNE_ARG
constexpr uint32_t kSlotBytes = 32768, kPieceBytes = 8192;
constexpr uint32_t kOffKg = 6 * kSlotBytes;
constexpr uint32_t kOffVg = kOffKg + 4096;
constexpr uint32_t kOffQg = kOffVg + 4096;
constexpr uint32_t kOffPg = kOffQg + 4096;
constexpr uint32_t kOffBar = kOffPg + 5 * 1536;
constexpr uint32_t kBarFull = kOffBar;
constexpr uint32_t kBarG = kBarFull + 56 * 8;
constexpr uint32_t kBarEmpty = kBarG + 8;
constexpr uint32_t kBarP = kBarEmpty + 8 * 8;
constexpr uint32_t kSmemBytes = kBarP + 6 * 8;
constexpr uint32_t kEmptyCounts = 0x4AA64995u;
constexpr uint32_t base = 1024;

constexpr float kScaleLog2 = 0.0625f * 1.4426950408889634f;

#define TLREC(i)
#define TLREC0(i)
struct Maps { CUtensorMap q, k, v, o, kg, vg, qg; };

constexpr int kInbox = 8 * 4 * 2;
__device__ __align__(128) uint4 g_part[kH * 8 * kInbox];

__device__ __forceinline__ uint32_t smem_u32(const void* p) { return (uint32_t)__cvta_generic_to_shared(p); }
__device__ __forceinline__ void mbar_init(uint32_t b, uint32_t c) {
    asm volatile("mbarrier.init.shared::cta.b64 [%0], %1;" ::"r"(b), "r"(c) : "memory");
}
__device__ __forceinline__ void mbar_expect(uint32_t b, uint32_t bytes) {
    asm volatile("mbarrier.arrive.expect_tx.shared::cta.b64 _, [%0], %1;" ::"r"(b), "r"(bytes) : "memory");
}
__device__ __forceinline__ void mbar_arrive(uint32_t b) {
    asm volatile("mbarrier.arrive.shared::cta.b64 _, [%0];" ::"r"(b) : "memory");
}
__device__ __forceinline__ void mbar_wait(uint32_t b) {
    asm volatile(
        "{\n.reg .pred p, q;\n.reg .u32 n;\nmov.u32 n, 0;\n"
        "LW%=:\n"
        "mbarrier.try_wait.parity.shared::cta.b64 p, [%0], 0;\n"
        "@p bra LD%=;\n"
        "add.u32 n, n, 1;\n"
        "setp.lt.u32 q, n, 4000000;\n"
        "@q bra LW%=;\n"
        "LD%=:\n}\n" ::"r"(b) : "memory");
}
__device__ __forceinline__ int ld_param(const int* p) {
    int v;
    asm volatile("ld.global.nc.s32 %0, [%1];" : "=r"(v) : "l"(p));
    return v;
}
__device__ __forceinline__ uint32_t gtime_lo() {
    uint32_t t;
    asm volatile("mov.u32 %0, %globaltimer_lo;" : "=r"(t));
    return t;
}
__device__ __forceinline__ void mbar_wait_until(uint32_t b, uint32_t due) {
    asm volatile(
        "{\n.reg .pred p, q;\n.reg .u32 t;\n.reg .s32 d;\n"
        "LW%=:\n"
        "mbarrier.test_wait.parity.shared::cta.b64 p, [%0], 0;\n"
        "@p bra LD%=;\n"
        "mov.u32 t, %globaltimer_lo;\n"
        "sub.s32 d, t, %1;\n"
        "setp.lt.s32 q, d, 0;\n"
        "@q bra LW%=;\n"
        "LD%=:\n}\n" ::"r"(b), "r"(due) : "memory");
}
__device__ __forceinline__ void mbar_arrive_n(uint32_t b, uint32_t n) {
    asm volatile("mbarrier.arrive.shared::cta.b64 _, [%0], %1;" ::"r"(b), "r"(n) : "memory");
}
__device__ __forceinline__ bool elect_one() {
    uint32_t p;
    asm volatile("{\n.reg .pred p;\nelect.sync _|p, 0xffffffff;\nselp.u32 %0, 1, 0, p;\n}\n" : "=r"(p));
    return p;
}
__device__ __forceinline__ uint64_t policy_evict_first() {
    uint64_t pol;
    asm("createpolicy.fractional.L2::evict_first.b64 %0, 1.0;" : "=l"(pol));
    return pol;
}
__device__ __forceinline__ void tma_load(uint32_t dst, const CUtensorMap* m, uint32_t bar, int row, int chunk,
                                         int head, uint64_t pol) {
    asm volatile(
        "cp.async.bulk.tensor.4d.shared::cluster.global.mbarrier::complete_tx::bytes.L2::cache_hint "
        "[%0], [%1, {%3,%4,%5,%6}], [%2], %7;" ::"r"(dst), "l"(m), "r"(bar), "r"(0), "r"(row), "r"(chunk),
        "r"(head), "l"(pol) : "memory");
}
__device__ __forceinline__ void tma_load_nohint(uint32_t dst, const CUtensorMap* m, uint32_t bar, int row,
                                                int chunk, int head) {
    asm volatile(
        "cp.async.bulk.tensor.4d.shared::cluster.global.mbarrier::complete_tx::bytes "
        "[%0], [%1, {%3,%4,%5,%6}], [%2];" ::"r"(dst), "l"(m), "r"(bar), "r"(0), "r"(row), "r"(chunk), "r"(head)
        : "memory");
}
__device__ __forceinline__ void tma_store_elect(uint32_t src, const CUtensorMap* m, int row, int chunk, int head) {
    asm volatile(
        "{\n.reg .pred p;\nelect.sync _|p, 0xffffffff;\n"
        "@p cp.async.bulk.tensor.4d.global.shared::cta.bulk_group [%1, {%2,%3,%4,%5}], [%0];\n}\n" ::"r"(src),
        "l"(m), "r"(0), "r"(row), "r"(chunk), "r"(head) : "memory");
}
__device__ __forceinline__ float ex2(float x) {
    float y;
    asm("ex2.approx.ftz.f32 %0, %1;" : "=f"(y) : "f"(x));
    return y;
}
__device__ __forceinline__ uint32_t pack_bf16(float lo, float hi) {
    uint32_t r;
    asm("cvt.rn.bf16x2.f32 %0, %1, %2;" : "=r"(r) : "f"(hi), "f"(lo));
    return r;
}
__device__ __forceinline__ uint32_t make_desc(uint32_t addr, uint32_t lbo) {
    return ((addr & 0x3FFFF) >> 4) | ((lbo >> 4) << 16);
}
constexpr uint32_t kDescHi1024 = (1024u >> 4) | (1u << 30), kDescHi0 = 1u << 30;
__device__ __forceinline__ void wg_fence() { asm volatile("wgmma.fence.sync.aligned;" ::: "memory"); }
__device__ __forceinline__ void wg_commit() { asm volatile("wgmma.commit_group.sync.aligned;" ::: "memory"); }
template <int N>
__device__ __forceinline__ void wg_wait() { asm volatile("wgmma.wait_group.sync.aligned %0;" ::"n"(N) : "memory"); }

#define F4(a, i) "+f"(a[i]), "+f"(a[i + 1]), "+f"(a[i + 2]), "+f"(a[i + 3])
#define F16(a, i) F4(a, i), F4(a, i + 4), F4(a, i + 8), F4(a, i + 12)

#define O4(a, i) "=f"(a[i]), "=f"(a[i + 1]), "=f"(a[i + 2]), "=f"(a[i + 3])
#define O16(a, i) O4(a, i), O4(a, i + 4), O4(a, i + 8), O4(a, i + 12)
#define ACC32 "{%0,%1,%2,%3,%4,%5,%6,%7,%8,%9,%10,%11,%12,%13,%14,%15," \
              "%16,%17,%18,%19,%20,%21,%22,%23,%24,%25,%26,%27,%28,%29,%30,%31}, "

__device__ __forceinline__ void wgmma_ss_n64(float (&d)[32], uint32_t da, uint32_t db) {
    asm volatile(
        "{\n.reg .pred p;\n.reg .b64 a, b;\nsetp.eq.b32 p, 0, 0;\n"
        "mov.b64 a, {%32, %34};\nmov.b64 b, {%33, %34};\n"
        "wgmma.mma_async.sync.aligned.m64n64k16.f32.bf16.bf16 " ACC32 "a, b, p, 1, 1, 0, 0;\n}\n"
        : F16(d, 0), F16(d, 16) : "r"(da), "r"(db), "n"(kDescHi1024));
}
__device__ __forceinline__ void wgmma_ss_n8(float (&d)[4], uint32_t da, uint32_t db) {
    asm volatile(
        "{\n.reg .pred p;\n.reg .b64 a, b;\nsetp.eq.b32 p, 0, 0;\n"
        "mov.b64 a, {%4, %6};\nmov.b64 b, {%5, %6};\n"
        "wgmma.mma_async.sync.aligned.m64n8k16.f32.bf16.bf16 {%0,%1,%2,%3}, a, b, p, 1, 1, 0, 0;\n}\n"
        : F4(d, 0) : "r"(da), "r"(db), "n"(kDescHi1024));
}
__device__ __forceinline__ void wgmma_rs_n64(float (&d)[32], uint32_t a0, uint32_t a1, uint32_t a2, uint32_t a3,
                                             uint32_t db) {
    asm volatile(
        "{\n.reg .pred p;\n.reg .b64 b;\nsetp.eq.b32 p, 0, 0;\n"
        "mov.b64 b, {%36, %37};\n"
        "wgmma.mma_async.sync.aligned.m64n64k16.f32.bf16.bf16 " ACC32 "{%32,%33,%34,%35}, b, p, 1, 1, 1;\n}\n"
        : F16(d, 0), F16(d, 16) : "r"(a0), "r"(a1), "r"(a2), "r"(a3), "r"(db), "n"(kDescHi1024));
}
__device__ __forceinline__ void wgmma_rs_n64_init(float (&d)[32], uint32_t a0, uint32_t a1, uint32_t a2, uint32_t a3,
                                                  uint32_t db) {
    asm volatile(
        "{\n.reg .pred p;\n.reg .b64 b;\nsetp.ne.b32 p, 0, 0;\n"
        "mov.b64 b, {%36, %37};\n"
        "wgmma.mma_async.sync.aligned.m64n64k16.f32.bf16.bf16 " ACC32 "{%32,%33,%34,%35}, b, p, 1, 1, 1;\n}\n"
        : O16(d, 0), O16(d, 16) : "r"(a0), "r"(a1), "r"(a2), "r"(a3), "r"(db), "n"(kDescHi0));
}
__device__ __forceinline__ void mma_16816(float (&d)[4], uint32_t a0, uint32_t a1, uint32_t a2, uint32_t a3,
                                          uint32_t b0, uint32_t b1) {
    asm(
        "mma.sync.aligned.m16n8k16.row.col.f32.bf16.bf16.f32 {%0,%1,%2,%3}, {%4,%5,%6,%7}, {%8,%9}, {%0,%1,%2,%3};"
        : F4(d, 0) : "r"(a0), "r"(a1), "r"(a2), "r"(a3), "r"(b0), "r"(b1));
}
__device__ __forceinline__ void ldsm_x4(uint32_t (&r)[4], uint32_t addr) {
    asm volatile("ldmatrix.sync.aligned.m8n8.x4.shared.b16 {%0,%1,%2,%3}, [%4];"
                 : "=r"(r[0]), "=r"(r[1]), "=r"(r[2]), "=r"(r[3]) : "r"(addr) : "memory");
}
__device__ __forceinline__ void ldsm_x4_t(uint32_t (&r)[4], uint32_t addr) {
    asm volatile("ldmatrix.sync.aligned.m8n8.x4.trans.shared.b16 {%0,%1,%2,%3}, [%4];"
                 : "=r"(r[0]), "=r"(r[1]), "=r"(r[2]), "=r"(r[3]) : "r"(addr) : "memory");
}
__device__ __forceinline__ void stsm_x4(uint32_t addr, uint32_t r0, uint32_t r1, uint32_t r2, uint32_t r3) {
    asm volatile("stmatrix.sync.aligned.m8n8.x4.shared.b16 [%0], {%1,%2,%3,%4};" ::"r"(addr), "r"(r0), "r"(r1),
                 "r"(r2), "r"(r3) : "memory");
}
__device__ __forceinline__ void stsm_x4_t(uint32_t addr, uint32_t r0, uint32_t r1, uint32_t r2, uint32_t r3) {
    asm volatile("stmatrix.sync.aligned.m8n8.x4.trans.shared.b16 [%0], {%1,%2,%3,%4};" ::"r"(addr), "r"(r0), "r"(r1),
                 "r"(r2), "r"(r3) : "memory");
}
__device__ __forceinline__ void sts_v4(uint32_t addr, uint32_t a, uint32_t b, uint32_t c, uint32_t d) {
    asm volatile("st.shared.v4.u32 [%0], {%1,%2,%3,%4};" ::"r"(addr), "r"(a), "r"(b), "r"(c), "r"(d) : "memory");
}
__device__ __forceinline__ uint4 lds_v4(uint32_t addr) {
    uint4 v;
    asm volatile("ld.shared.v4.u32 {%0,%1,%2,%3}, [%4];" : "=r"(v.x), "=r"(v.y), "=r"(v.z), "=r"(v.w) : "r"(addr) : "memory");
    return v;
}
__device__ __forceinline__ uint32_t movm_t(uint32_t a) {
    uint32_t d;
    asm volatile("movmatrix.sync.aligned.m8n8.trans.b16 %0, %1;" : "=r"(d) : "r"(a));
    return d;
}
__device__ __forceinline__ void st_part(uint4* p, float a, float b, float c, float d, bool on) {
    asm volatile(
        "{\n.reg .pred p;\nsetp.ne.b32 p, %5, 0;\n"
        "@p st.relaxed.gpu.global.v4.u32 [%0], {%1,%2,%3,%4};\n}\n" ::"l"(p), "r"(__float_as_uint(a) | 1u),
        "r"(__float_as_uint(b) | 1u), "r"(__float_as_uint(c) | 1u), "r"(__float_as_uint(d) | 1u), "r"((int)on)
        : "memory");
}
__device__ __forceinline__ void clr_part(uint4* p, bool on) {
    asm volatile(
        "{\n.reg .pred p;\nsetp.ne.b32 p, %2, 0;\n"
        "@p st.relaxed.gpu.global.v4.u32 [%0], {%1,%1,%1,%1};\n}\n" ::"l"(p), "r"(0), "r"((int)on) : "memory");
}
__device__ __forceinline__ void red_bf16x8(__nv_bfloat16* p, const uint4& v, bool on) {
    asm volatile(
        "{\n.reg .pred p;\nsetp.ne.b32 p, %5, 0;\n"
        "@p red.relaxed.gpu.global.add.noftz.v4.bf16x2 [%0], {%1,%2,%3,%4};\n}\n" ::"l"(p), "r"(v.x), "r"(v.y),
        "r"(v.z), "r"(v.w), "r"((int)on) : "memory");
}
__device__ __forceinline__ float dec(uint32_t u) { return __uint_as_float(u); }
__device__ __forceinline__ uint4 ld_part(const uint4* p) {
    uint4 v;
    asm volatile("ld.relaxed.gpu.global.v4.u32 {%0,%1,%2,%3}, [%4];"
                 : "=r"(v.x), "=r"(v.y), "=r"(v.z), "=r"(v.w) : "l"(p) : "memory");
    return v;
}
__device__ __forceinline__ bool ready(const uint4& v) { return v.x && v.y && v.z && v.w; }

__device__ __forceinline__ void generic_rows(const __nv_bfloat16* q, const __nv_bfloat16* k, const __nv_bfloat16* v,
                                          __nv_bfloat16* out, int head, int r0, int W, int G) {
    const int warp = threadIdx.x >> 5, lane = threadIdx.x & 31;
    const size_t hb = (size_t)head * kS * kD;
    #pragma unroll 1
    for (int i = r0 + warp; i < r0 + 256; i += 8) {
        float qf[8], o[8];
        {
            uint4 u = *reinterpret_cast<const uint4*>(q + hb + (size_t)i * kD + lane * 8);
            const __nv_bfloat16* e = reinterpret_cast<const __nv_bfloat16*>(&u);
#pragma unroll
            for (int x = 0; x < 8; x++) { qf[x] = __bfloat162float(e[x]); o[x] = 0.f; }
        }
        const bool none = (W < 0) && (G <= 0);
        float m = -INFINITY, l = 0.f;
#pragma unroll 1
        for (int j = 0; j < kS; j++) {
            const long long dist = (long long)i - j;
            const bool on = (dist <= W && dist >= -(long long)W) || i < G || j < G;
            if (!on && !none) continue;
            float s = -1.0e9f;
            if (on) {
                uint4 u = *reinterpret_cast<const uint4*>(k + hb + (size_t)j * kD + lane * 8);
                const __nv_bfloat16* e = reinterpret_cast<const __nv_bfloat16*>(&u);
                s = 0.f;
#pragma unroll
                for (int x = 0; x < 8; x++) s += qf[x] * __bfloat162float(e[x]);
#pragma unroll
                for (int x = 16; x; x >>= 1) s += __shfl_xor_sync(0xffffffffu, s, x);
                s *= 0.0625f;
            }
            const float mn = fmaxf(m, s);
            const float a = __expf(m - mn), p = __expf(s - mn);
            uint4 u = *reinterpret_cast<const uint4*>(v + hb + (size_t)j * kD + lane * 8);
            const __nv_bfloat16* e = reinterpret_cast<const __nv_bfloat16*>(&u);
#pragma unroll
            for (int x = 0; x < 8; x++) o[x] = o[x] * a + p * __bfloat162float(e[x]);
            l = l * a + p;
            m = mn;
        }
        const float inv = 1.f / l;
        uint4 r;
        r.x = pack_bf16(o[0] * inv, o[1] * inv);
        r.y = pack_bf16(o[2] * inv, o[3] * inv);
        r.z = pack_bf16(o[4] * inv, o[5] * inv);
        r.w = pack_bf16(o[6] * inv, o[7] * inv);
        *reinterpret_cast<uint4*>(out + hb + (size_t)i * kD + lane * 8) = r;
    }
}

__device__ __forceinline__ void store_chunk(uint32_t stage, const CUtensorMap* mo, int row, int c, int head,
                                            const float (&o)[32], float r0, float r1, int lane) {
    const uint32_t dst = stage + c * 8192 + (lane & 15) * 128 + (((lane >> 4) ^ (lane & 7)) << 4);
#pragma unroll
    for (int x = 0; x < 4; x++)
        stsm_x4(dst ^ (x << 5), pack_bf16(o[8 * x] * r0, o[8 * x + 1] * r0),
                pack_bf16(o[8 * x + 2] * r1, o[8 * x + 3] * r1), pack_bf16(o[8 * x + 4] * r0, o[8 * x + 5] * r0),
                pack_bf16(o[8 * x + 6] * r1, o[8 * x + 7] * r1));
    asm volatile("fence.proxy.async.shared::cta;" ::: "memory");
    __syncwarp();
    tma_store_elect(stage + c * 8192, mo, row, c, head);
}

__device__ __forceinline__ void mask_init(float (&s)[32], int i0, int cq, int W, int G) {
    const int lo0 = max(i0 - W, G) - cq, hi0 = min(i0 + W, kS - 1) - cq;
    const int lo1 = max(i0 + 8 - W, G) - cq, hi1 = min(i0 + 8 + W, kS - 1) - cq;
#pragma unroll
    for (int x = 0; x < 16; x++) {
        const int c = 8 * (x >> 1) + (x & 1), i = 4 * (x >> 1) + (x & 1);
        s[i] = (c >= lo0 && c <= hi0) ? 0.f : -INFINITY;
        s[i + 2] = (c >= lo1 && c <= hi1) ? 0.f : -INFINITY;
    }
}
template <int R>
__device__ __forceinline__ float row_max(const float (&sa)[32], const float (&sb)[32], const float (&sg)[4]) {
    float m0 = sg[2 * R], m1 = sg[2 * R + 1];
#pragma unroll
    for (int x = 0; x < 16; x++) {
        const int i = 4 * (x >> 1) + 2 * R + (x & 1);
        m0 = fmaxf(m0, sa[i]);
        m1 = fmaxf(m1, sb[i]);
    }
    m0 = fmaxf(m0, m1);
    m0 = fmaxf(m0, __shfl_xor_sync(0xffffffffu, m0, 1));
    return fmaxf(m0, __shfl_xor_sync(0xffffffffu, m0, 2));
}
template <int R>
__device__ __forceinline__ float row_exp(const float (&sa)[32], const float (&sb)[32], const float (&sg)[4],
                                         float mx, uint32_t (&pa)[16], uint32_t (&pb)[16], uint32_t& pg) {
    const float b = -mx * kScaleLog2;
    float l0 = ex2(fmaf(sg[2 * R], kScaleLog2, b)), l1 = ex2(fmaf(sg[2 * R + 1], kScaleLog2, b));
    pg = pack_bf16(l0, l1);
#pragma unroll
    for (int n = 0; n < 8; n++) {
        const int i = 4 * n + 2 * R;
        const float p0 = ex2(fmaf(sa[i], kScaleLog2, b)), p1 = ex2(fmaf(sa[i + 1], kScaleLog2, b));
        const float p2 = ex2(fmaf(sb[i], kScaleLog2, b)), p3 = ex2(fmaf(sb[i + 1], kScaleLog2, b));
        l0 += p0 + p1;
        l1 += p2 + p3;
        pa[2 * n + R] = pack_bf16(p0, p1);
        pb[2 * n + R] = pack_bf16(p2, p3);
    }
    return l0 + l1;
}
__device__ __forceinline__ void pv_chunk(float (&o)[32], const uint32_t (&p)[16], uint32_t bar, uint32_t dv) {
    mbar_wait(bar);
    wg_fence();
#pragma unroll
    for (int kk = 0; kk < 4; kk++)
        wgmma_rs_n64(o, p[4 * kk], p[4 * kk + 1], p[4 * kk + 2], p[4 * kk + 3], dv + ((kk * 2048) >> 4));
}

__device__ __forceinline__ void local_tile(int t, int qrow, int krow, int dr, int W, int G, int warp, int lane,
                                           const CUtensorMap* mo, int head, int tl_c0) {
    const uint32_t sQ = base + (uint32_t)(t == 3 ? 0 : t) * kSlotBytes;
    const uint32_t fT = base + kBarFull + 3 * t * 32;
    const uint32_t dQ = make_desc(sQ, 16);
    const uint32_t dKb = make_desc(base + (uint32_t)(4 - (t & 1)) * kSlotBytes, 16);
    const uint32_t dK = make_desc(base + (uint32_t)(3 + (t & 1)) * kSlotBytes, 16);
    const uint32_t dKg = make_desc(base + kOffKg, 16);
    const int row = qrow + warp * 16, g0 = 2 * (lane & 3), i0 = row + (lane >> 2);
    float sa[32], sb[32], sg[4];
    mask_init(sa, i0, krow + g0, W, G);
    mask_init(sb, i0, krow + dr + g0, W, G);
    sg[0] = sg[2] = g0 < G ? 0.f : -INFINITY;
    sg[1] = sg[3] = g0 + 1 < G ? 0.f : -INFINITY;
    {
        const uint32_t fK = t ? fT - 32 : fT, fQ = t == 3 ? fT + 64 : fT + 32;
#pragma unroll 1
        for (int c = 0; c < 4; c++) {
            const uint32_t qc = dQ + c * 512, kc = dK + c * 512, gc = dKg + c * 64;
            mbar_wait(fK + 8 * c);
            mbar_wait(fQ + 8 * c);
            wg_fence();
#pragma unroll
            for (int x = 0; x < 4; x++) {
                wgmma_ss_n64(sa, qc + 2 * x, kc + 2 * x);
                wgmma_ss_n8(sg, qc + 2 * x, gc + 2 * x);
            }
            wg_commit();
            if (t == 3) {
                mbar_wait(fT + 32 + 8 * c);
                wg_fence();
#pragma unroll
                for (int x = 0; x < 4; x++) wgmma_ss_n64(sb, qc + 2 * x, dKb + c * 512 + 2 * x);
                wg_commit();
            }
        }
        wg_wait<0>();
        if (t < 3) {
            if (lane == 0) mbar_arrive(base + kBarEmpty + 8 * t);
#pragma unroll 1
            for (int c = 0; c < 4; c++) {
                mbar_wait(fT + 64 + 8 * c);
                wg_fence();
#pragma unroll
                for (int x = 0; x < 4; x++) wgmma_ss_n64(sb, dQ + c * 512 + 2 * x, dKb + c * 512 + 2 * x);
                wg_commit();
            }
            wg_wait<0>();
            if (t < 2 && lane == 0) mbar_arrive(base + kBarEmpty + 8 * (t + 1));
        }
    }
    if (warp == 0) TLREC0(16 + 4 * t);
    uint32_t pa[16], pb[16], pg0, pg1;
    const float mx0 = row_max<0>(sa, sb, sg);
    const float mx1 = row_max<1>(sa, sb, sg);
    float l0 = row_exp<0>(sa, sb, sg, mx0, pa, pb, pg0);
    float l1 = row_exp<1>(sa, sb, sg, mx1, pa, pb, pg1);
    if (warp == 0) TLREC0(17 + 4 * t);

    float o[4][32];
    const uint32_t dV = make_desc(base + 5 * kSlotBytes, 8192);
    {
        const uint32_t dVg = make_desc(base + kOffVg, 1024);
        uint32_t z0, z1;
        asm volatile("shr.u32 %0, %2, 8;\nshr.u32 %1, %3, 8;" : "=r"(z0), "=r"(z1) : "r"(G), "r"(W));
        wg_fence();
#pragma unroll
        for (int c = 0; c < 4; c++) wgmma_rs_n64_init(o[c], pg0, pg1, z0, z1, dVg + ((c * 1024) >> 4));
        wg_commit();
    }
    l0 += __shfl_xor_sync(0xffffffffu, l0, 1);
    l1 += __shfl_xor_sync(0xffffffffu, l1, 1);
    l0 += __shfl_xor_sync(0xffffffffu, l0, 2);
    l1 += __shfl_xor_sync(0xffffffffu, l1, 2);
    const float r0 = i0 < G ? 0.f : __fdividef(1.f, l0), r1 = __fdividef(1.f, l1);
    const uint32_t stage = sQ + warp * 2048;
    if (t < 3) {
#pragma unroll
        for (int c = 0; c < 4; c++) pv_chunk(o[c], pa, fT + 96 + 8 * c, dV + ((c * 8192) >> 4));
        wg_commit();
        wg_wait<0>();
        if (lane == 0) mbar_arrive(base + kBarEmpty + 8 * (4 + t));
        if (warp == 0) TLREC0(18 + 4 * t);
        const uint32_t fstep = t < 2 ? 8 : 16;
#pragma unroll
        for (int c = 0; c < 4; c++) {
            pv_chunk(o[c], pb, fT + 192 + fstep * c, dV + ((c * 8192) >> 4));
            wg_commit();
            wg_wait<0>();
            if (c == 3 && t < 2 && lane == 0) mbar_arrive(base + kBarEmpty + 8 * (5 + t));
            store_chunk(stage, mo, row, c, head, o[c], r0, r1, lane);
        }
    } else {
        const uint32_t dV4 = make_desc(base + 1 * kSlotBytes, 8192), fV = base + kBarFull + 8 * 48;
        pv_chunk(o[0], pa, fV, dV);
#pragma unroll
        for (int c = 0; c < 4; c++) {
            pv_chunk(o[c], pb, fV + 16 * c + 8, dV4 + ((c * 8192) >> 4));
            wg_commit();
            if (c < 3) {
                pv_chunk(o[c + 1], pa, fV + 16 * c + 16, dV + (((c + 1) * 8192) >> 4));
                wg_commit();
                wg_wait<1>();
            } else {
                wg_wait<0>();
            }
            if (c == 0 && warp == 0) TLREC0(58);
            if (c == 3 && warp == 0) TLREC0(59);
            store_chunk(stage, mo, row, c, head, o[c], r0, r1, lane);
            if (c == 1 && warp == 0) TLREC0(30);
        }
    }
}

__global__ void __launch_bounds__(kThreads, 1)
attn_kernel(const int* __restrict__ p_win, const int* __restrict__ p_glob, uint4* __restrict__ part,
            __nv_bfloat16* __restrict__ out, const __nv_bfloat16* __restrict__ q,
            const __nv_bfloat16* __restrict__ k, const __nv_bfloat16* __restrict__ v,
            const __grid_constant__ Maps maps TUNE_PARAM) {
    extern __shared__ uint8_t smem_raw[];
    const int tl_c0 = 0;
    const uint32_t t_start = gtime_lo();
    if (smem_u32(smem_raw) != base) __trap();
    const int warp = __shfl_sync(0xffffffffu, threadIdx.x >> 5, 0), lane = threadIdx.x & 31;
    const int head = blockIdx.x >> 3, chunk = blockIdx.x & 7;
    const int r0 = chunk * 256;
    const bool bwd = chunk & 1;
    const int rq = bwd ? r0 + 192 : r0, rk = bwd ? r0 + 224 : r0 - 32, dr = bwd ? -64 : 64;

    const bool leader = elect_one();
    if (warp < kBurstPieces && leader) {
        const uint32_t fb = base + kBarFull + 8 * warp;
        mbar_init(fb, 1);
        mbar_expect(fb, kPieceBytes);
        tma_load(base + (warp < 4 ? 3 * kSlotBytes : 0) + (warp & 3) * kPieceBytes, warp < 4 ? &maps.k : &maps.q, fb,
                 warp < 4 ? rk : rq, warp & 3, head, policy_evict_first());
    }
    int W = 0, G = 0;
    if (warp != 10) { W = ld_param(p_win); G = ld_param(p_glob); }
    if (leader) {
        if (warp == 11) {
            mbar_init(base + kBarG, 1);
#pragma unroll
            for (int b = 0; b < 8; b++) mbar_init(base + kBarEmpty + 8 * b, (kEmptyCounts >> (4 * b)) & 15);
#pragma unroll
            for (int b = 0; b < 6; b++) mbar_init(base + kBarP + 8 * b, 1);
            mbar_expect(base + kBarG, 3 * 4096);
            tma_load_nohint(base + kOffKg, &maps.kg, base + kBarG, 0, 0, head);
            tma_load_nohint(base + kOffQg, &maps.qg, base + kBarG, 0, 0, head);
            tma_load_nohint(base + kOffVg, &maps.vg, base + kBarG, 0, 0, head);
        } else if (warp == 10) {
#pragma unroll
            for (int b = kBurstPieces; b < 32; b++) mbar_init(base + kBarFull + 8 * b, 1);
        } else if (warp == 9) {
#pragma unroll
            for (int b = 32; b < 56; b++) mbar_init(base + kBarFull + 8 * b, 1);
        }
    }
    asm volatile("fence.mbarrier_init.release.cluster;" ::: "memory");
    __syncthreads();

    if (warp < 8) {
        asm volatile("setmaxnreg.inc.sync.aligned.u32 200;");
        W = __shfl_sync(0xffffffffu, W, 0);
        G = __shfl_sync(0xffffffffu, G, 0);
        if (W < 0 || W > kMaxWin || G < 0 || G > kMaxGlob) {
            generic_rows(q, k, v, out, head, r0, W, G);
            return;
        }
        const int wq = warp & 3;
        mbar_wait(base + kBarG);
#pragma unroll 1
        for (int t = warp >> 2; t < 4; t += 2) {
            local_tile(t, rq + dr * t, rk + dr * t, dr, W, G, wq, lane, &maps.o, head, tl_c0);
            if (wq == 0) TLREC0(19 + 4 * t);
            asm volatile("cp.async.bulk.commit_group;" ::: "memory");
            if (t < 2) {
                asm volatile("cp.async.bulk.wait_group 0;" ::: "memory");
                __syncwarp();
                if (lane == 0) mbar_arrive(base + kBarEmpty + 8 * (t ? 3 : 7));
            }
        }
        asm volatile("cp.async.bulk.wait_group.read 0;" ::: "memory");
        if (wq == 0) TLREC0(32 + (warp >> 2));
    } else {
        asm volatile("setmaxnreg.dec.sync.aligned.u32 104;");
        if (warp != 10) {
            W = __shfl_sync(0xffffffffu, W, 0);
            G = __shfl_sync(0xffffffffu, G, 0);
            if (W < 0 || W > kMaxWin || G < 0 || G > kMaxGlob) {
                if (warp == 8) {
                    if (lane < 8) mbar_arrive_n(base + kBarEmpty + 8 * lane, (kEmptyCounts >> (4 * lane)) & 15);
#pragma unroll 1
                    for (int x = 0; x < 57; x++) mbar_wait(base + kBarFull + 8 * x);
                }
                return;
            }
        }
        const uint32_t edge0 = bwd ? 0 : 4096;
        const bool pub = 2 * (lane & 3) < G;
        if (warp == 11) {
            float m0 = -INFINITY, m1 = -INFINITY, l0 = 0.f, l1 = 0.f;
            const uint32_t aQ = base + kOffQg + (lane & 7) * 128 + (((lane >> 3) ^ (lane & 7)) << 4);
            const uint32_t lK = base + 3 * kSlotBytes + (lane & 15) * 128 + (((lane >> 4) ^ (lane & 7)) << 4);
            uint4* const rml =
                part + (head * 8 + (lane >> 3)) * kInbox + (chunk * 4 + (lane & 3)) * 2 + ((lane >> 2) & 1);
            clr_part(rml, pub);
            clr_part(rml + 4 * kInbox, pub);
            mbar_wait(base + kBarG);
#pragma unroll 1
            for (int j = 0; j < 5; j++) {
                const bool full = j != 0 && j != 4;
                const uint32_t aK = lK + (j & 1) * kSlotBytes + (full ? 0 : j ? edge0 ^ 4096 : edge0);
                const uint32_t aK2 = aK + (full ? 4096 : 0);
                const uint32_t fK = base + kBarFull + (j == 4 ? 10 : j ? 3 * j - 1 : 0) * 32;
                float s[4][4];
#pragma unroll
                for (int i = 0; i < 4; i++) s[i][0] = s[i][1] = s[i][2] = s[i][3] = 0.f;
#pragma unroll
                for (int c = 0; c < 4; c++) {
                    uint32_t qb[2][4];
                    ldsm_x4(qb[0], aQ + c * 1024);
                    ldsm_x4(qb[1], (aQ ^ 64) + c * 1024);
                    mbar_wait(fK + 8 * c);
#pragma unroll
                    for (int x = 0; x < 4; x++) {
                        uint32_t f[4][4];
                        ldsm_x4(f[0], (aK ^ (x << 5)) + c * 8192);
                        ldsm_x4(f[1], (aK ^ (x << 5)) + c * 8192 + 2048);
                        ldsm_x4(f[2], (aK2 ^ (x << 5)) + c * 8192);
                        ldsm_x4(f[3], (aK2 ^ (x << 5)) + c * 8192 + 2048);
#pragma unroll
                        for (int i = 0; i < 4; i++)
                            mma_16816(s[i], f[i][0], f[i][1], f[i][2], f[i][3], qb[x >> 1][2 * (x & 1)],
                                      qb[x >> 1][2 * (x & 1) + 1]);
                    }
                }
                __syncwarp();
                if (j < 3 && lane == 0) mbar_arrive(base + kBarEmpty + 8 * j);
#pragma unroll
                for (int x = 0; x < 4; x++) {
                    s[2][x] = full ? s[2][x] : -INFINITY;
                    s[3][x] = full ? s[3][x] : -INFINITY;
                }
                float mx0 = m0, mx1 = m1;
#pragma unroll
                for (int i = 0; i < 4; i++) {
                    mx0 = fmaxf(mx0, fmaxf(s[i][0], s[i][2]));
                    mx1 = fmaxf(mx1, fmaxf(s[i][1], s[i][3]));
                }
#pragma unroll
                for (int x = 4; x < 32; x <<= 1) {
                    mx0 = fmaxf(mx0, __shfl_xor_sync(0xffffffffu, mx0, x));
                    mx1 = fmaxf(mx1, __shfl_xor_sync(0xffffffffu, mx1, x));
                }
                const float b0 = mx0 == -INFINITY ? 0.f : -mx0 * kScaleLog2;
                const float b1 = mx1 == -INFINITY ? 0.f : -mx1 * kScaleLog2;
                const float a0 = ex2(fmaf(m0, kScaleLog2, b0)), a1 = ex2(fmaf(m1, kScaleLog2, b1));
                m0 = mx0;
                m1 = mx1;
                l0 *= a0;
                l1 *= a1;
                uint32_t pf[8];
#pragma unroll
                for (int i = 0; i < 4; i++) {
                    const float p0 = ex2(fmaf(s[i][0], kScaleLog2, b0)), p1 = ex2(fmaf(s[i][1], kScaleLog2, b1));
                    const float p2 = ex2(fmaf(s[i][2], kScaleLog2, b0)), p3 = ex2(fmaf(s[i][3], kScaleLog2, b1));
                    l0 += p0 + p2;
                    l1 += p1 + p3;
                    pf[2 * i] = movm_t(pack_bf16(p0, p1));
                    pf[2 * i + 1] = movm_t(pack_bf16(p2, p3));
                }
                const uint32_t aP = base + kOffPg + j * 1536 + lane * 16;
                sts_v4(aP, pf[0], pf[1], pf[2], pf[3]);
                sts_v4(aP + 512, pf[4], pf[5], pf[6], pf[7]);
                sts_v4(aP + 1024, __float_as_uint(a0), __float_as_uint(a1), 0u, 0u);
                __syncwarp();
                if (lane == 0) mbar_arrive(base + kBarP + 8 * j);
                if (j >= 3) TLREC0(34 + 2 * (j - 3));
            }
#pragma unroll
            for (int x = 4; x < 32; x <<= 1) {
                l0 += __shfl_xor_sync(0xffffffffu, l0, x);
                l1 += __shfl_xor_sync(0xffffffffu, l1, x);
            }
            st_part(rml, m0, m1, l0, l1, pub);
            st_part(rml + 4 * kInbox, m0, m1, l0, l1, pub);
            TLREC0(40);
            uint4* const in = part + (head * 8 + chunk) * kInbox + lane * 2;
            uint4 ml = make_uint4(1, 1, 1, 1);
            int it = 0;
            do {
                if (pub) ml = ld_part(in);
            } while (!__all_sync(0xffffffffu, ready(ml)) && ++it < 2000000);
            TLREC0(37);
            float M0 = dec(ml.x), M1 = dec(ml.y);
#pragma unroll
            for (int x = 4; x < 32; x <<= 1) {
                M0 = fmaxf(M0, __shfl_xor_sync(0xffffffffu, M0, x));
                M1 = fmaxf(M1, __shfl_xor_sync(0xffffffffu, M1, x));
            }
            float L0 = ex2((dec(ml.x) - M0) * kScaleLog2) * dec(ml.z);
            float L1 = ex2((dec(ml.y) - M1) * kScaleLog2) * dec(ml.w);
#pragma unroll
            for (int x = 4; x < 32; x <<= 1) {
                L0 += __shfl_xor_sync(0xffffffffu, L0, x);
                L1 += __shfl_xor_sync(0xffffffffu, L1, x);
            }
            const float f0 = __fdividef(ex2((m0 - M0) * kScaleLog2), L0);
            const float f1 = __fdividef(ex2((m1 - M1) * kScaleLog2), L1);
            sts_v4(base + kOffPg + 4 * 1536 + 512 + lane * 16, __float_as_uint(f0), __float_as_uint(f1), 0u, 0u);
            __syncwarp();
            if (lane == 0) mbar_arrive(base + kBarP + 8 * 5);
            clr_part(in, pub);
            clr_part(in + 1, pub);
            TLREC0(44);
        } else if (warp < 10) {
            const int g = warp - 8;
            float og[4][2][4];
#pragma unroll
            for (int i = 0; i < 8; i++) og[i >> 1][i & 1][0] = og[i >> 1][i & 1][1] = og[i >> 1][i & 1][2] = og[i >> 1][i & 1][3] = 0.f;
            const uint32_t lV = base + ((lane & 7) + ((lane >> 4) << 3)) * 128 +
                                (((4 * g + ((lane >> 3) & 1)) ^ (lane & 7)) << 4);
            const uint32_t aP = base + kOffPg + lane * 16;
#pragma unroll 1
            for (int j = 0; j < 3; j++) {
                const uint32_t aV = lV + 5 * kSlotBytes + (j ? 0 : edge0);
                const uint32_t aV2 = aV + (j ? 4096 : 0);
                const uint32_t fV = base + kBarFull + (3 * j + 3) * 32;
                mbar_wait(base + kBarP + 8 * j);
                const uint4 p0 = lds_v4(aP + j * 1536), p1 = lds_v4(aP + j * 1536 + 512);
                const uint4 al = lds_v4(aP + j * 1536 + 1024);
                const float a0 = __uint_as_float(al.x), a1 = __uint_as_float(al.y);
#pragma unroll
                for (int i = 0; i < 8; i++) {
                    float(&t)[4] = og[i >> 1][i & 1];
                    t[0] *= a0; t[1] *= a1; t[2] *= a0; t[3] *= a1;
                }
#pragma unroll
                for (int c = 0; c < 4; c++) {
                    mbar_wait(fV + 8 * c);
                    uint32_t f[8][4];
#pragma unroll
                    for (int x = 0; x < 8; x++)
                        ldsm_x4_t(f[x], ((x < 4 ? aV : aV2) ^ ((x & 1) << 5)) + c * 8192 + ((x >> 1) & 1) * 2048);
#pragma unroll
                    for (int x = 0; x < 8; x++) {
                        const int kk = x >> 1;
                        mma_16816(og[c][x & 1], f[x][0], f[x][1], f[x][2], f[x][3],
                                  kk == 0 ? p0.x : kk == 1 ? p0.z : kk == 2 ? p1.x : p1.z,
                                  kk == 0 ? p0.y : kk == 1 ? p0.w : kk == 2 ? p1.y : p1.w);
                    }
                }
                __syncwarp();
                if (lane == 0) mbar_arrive(base + kBarEmpty + 8 * (4 + j));
                if (g == 1 && j == 2) TLREC0(35);
            }
            {
                const uint32_t aV = lV + 5 * kSlotBytes, aV4 = lV + 1 * kSlotBytes + (edge0 ^ 4096);
                const uint32_t fV = base + kBarFull + 8 * 48;
                mbar_wait(base + kBarP + 8 * 4);
                const uint4 p0 = lds_v4(aP + 3 * 1536), p1 = lds_v4(aP + 3 * 1536 + 512);
                const uint4 al = lds_v4(aP + 3 * 1536 + 1024);
                const uint4 p4 = lds_v4(aP + 4 * 1536), a4 = lds_v4(aP + 4 * 1536 + 1024);
#pragma unroll
                for (int i = 0; i < 8; i++) {
                    float(&t)[4] = og[i >> 1][i & 1];
                    t[0] *= __uint_as_float(al.x); t[1] *= __uint_as_float(al.y);
                    t[2] *= __uint_as_float(al.x); t[3] *= __uint_as_float(al.y);
                }
                const uint32_t aT = base + kOffPg + g * 1536;
                __nv_bfloat16* const op = out + ((size_t)head * kS + (lane >> 2)) * kD + g * 32 + 8 * (lane & 3);
                const bool red_on = (lane >> 2) < G;
                float f0 = 0.f, f1 = 0.f;
#pragma unroll
                for (int c = 0; c < 4; c++) {
                    if (c == 3) {
                        mbar_wait(base + kBarP + 8 * 5);
                        const uint4 fs = lds_v4(aP + 4 * 1536 + 512);
                        f0 = __uint_as_float(fs.x);
                        f1 = __uint_as_float(fs.y);
#pragma unroll
                        for (int y = 0; y < 3; y++)
                            stsm_x4_t(aT + y * 512 + (lane & 7) * 64 + (lane >> 3) * 16,
                                      pack_bf16(og[y][0][0] * f0, og[y][0][1] * f1), pack_bf16(og[y][0][2] * f0, og[y][0][3] * f1),
                                      pack_bf16(og[y][1][0] * f0, og[y][1][1] * f1), pack_bf16(og[y][1][2] * f0, og[y][1][3] * f1));
                        __syncwarp();
#pragma unroll
                        for (int y = 0; y < 3; y++) red_bf16x8(op + y * 64, lds_v4(aT + y * 512 + lane * 16), red_on);
                        __syncwarp();
                    }
                    float tm[2][4];
#pragma unroll
                    for (int x = 0; x < 2; x++) tm[x][0] = tm[x][1] = tm[x][2] = tm[x][3] = 0.f;
                    mbar_wait(fV + 16 * c);
                    uint32_t f[8][4];
#pragma unroll
                    for (int x = 0; x < 8; x++) ldsm_x4_t(f[x], (aV ^ ((x & 1) << 5)) + c * 8192 + (x >> 1) * 2048);
#pragma unroll
                    for (int x = 0; x < 4; x++) {
                        mma_16816(og[c][x & 1], f[x][0], f[x][1], f[x][2], f[x][3], x < 2 ? p0.x : p0.z,
                                  x < 2 ? p0.y : p0.w);
                        mma_16816(tm[x & 1], f[x + 4][0], f[x + 4][1], f[x + 4][2], f[x + 4][3], x < 2 ? p1.x : p1.z,
                                  x < 2 ? p1.y : p1.w);
                    }
#pragma unroll
                    for (int x = 0; x < 2; x++) {
#pragma unroll
                        for (int y = 0; y < 4; y++) {
                            og[c][x][y] = (og[c][x][y] + tm[x][y]) * __uint_as_float((y & 1) ? a4.y : a4.x);
                            tm[x][y] = 0.f;
                        }
                    }
                    mbar_wait(fV + 16 * c + 8);
#pragma unroll
                    for (int x = 0; x < 4; x++) ldsm_x4_t(f[x], (aV4 ^ ((x & 1) << 5)) + c * 8192 + (x >> 1) * 2048);
#pragma unroll
                    for (int x = 0; x < 2; x++) {
                        mma_16816(og[c][x], f[x][0], f[x][1], f[x][2], f[x][3], p4.x, p4.y);
                        mma_16816(tm[x], f[x + 2][0], f[x + 2][1], f[x + 2][2], f[x + 2][3], p4.z, p4.w);
                    }
#pragma unroll
                    for (int x = 0; x < 2; x++)
#pragma unroll
                        for (int y = 0; y < 4; y++) og[c][x][y] += tm[x][y];
                }
                stsm_x4_t(aT + (lane & 7) * 64 + (lane >> 3) * 16, pack_bf16(og[3][0][0] * f0, og[3][0][1] * f1),
                          pack_bf16(og[3][0][2] * f0, og[3][0][3] * f1), pack_bf16(og[3][1][0] * f0, og[3][1][1] * f1),
                          pack_bf16(og[3][1][2] * f0, og[3][1][3] * f1));
                __syncwarp();
                red_bf16x8(op + 3 * 64, lds_v4(aT + lane * 16), red_on);
            }
            if (g == 1) TLREC0(41);
        } else {
            if (elect_one()) {
                TLREC(1);
                const uint64_t pol = policy_evict_first();
                uint32_t due = t_start + kPace0 + 6 * kPace;
#pragma unroll 1
                for (int blk = kBurstPieces >> 2; blk < 14; blk++) {
                    const int ty = (int)(kBlkType >> (4 * blk)) & 15, idx = (int)(kBlkIdx >> (4 * blk)) & 15;
                    const int ew = (int)(kBlkWait >> (4 * blk)) & 15;
                    const bool mix = blk >= 12;
                    const uint32_t fb = base + kBarFull + 32 * blk;
                    const uint32_t dst = base + ((uint32_t)(kBlkSlot >> (4 * blk)) & 15) * kSlotBytes;
                    const CUtensorMap* const map = &maps.q + ty;
                    const int row = (ty ? rk : rq) + dr * idx;
#pragma unroll
                    for (int c = 0; c < 4; c++) {
                        if (4 * blk + c >= kBurstPieces) {
                            const int col = mix ? 2 * (blk - 12) + (c >> 1) : c;
                            const bool v4 = mix && (c & 1);
                            if (4 * blk + c >= kFreePieces) mbar_wait_until(fb + 8 * (c - kWindowPieces), due);
                            due += (((idx == 0 || idx == 4) && ty) || v4) ? kPace / 2 : kPace;
                            if (((c - kWindowPieces) & 3) == 3) TLREC(2 + ((4 * blk + c - kWindowPieces) >> 2));
                            if (c == 0 && ew != 15) mbar_wait(base + kBarEmpty + 8 * ew);
                            if (c == 1 && blk == 12) mbar_wait(base + kBarEmpty + 8 * 3);
                            mbar_expect(fb + 8 * c, kPieceBytes);
                            tma_load(dst - (v4 ? 4 * kSlotBytes : 0) + col * kPieceBytes, map, fb + 8 * c,
                                     row + (v4 ? dr : 0), col, head, pol);
                            if (c == 0 && blk >= 6) TLREC(48 + blk - 6);
                        }
                    }
                }
            }
        }
    }
}

typedef CUresult (*EncodeTiledFn)(CUtensorMap*, CUtensorMapDataType, cuuint32_t, void*, const cuuint64_t*,
                                  const cuuint64_t*, const cuuint32_t*, const cuuint32_t*, CUtensorMapInterleave,
                                  CUtensorMapSwizzle, CUtensorMapL2promotion, CUtensorMapFloatOOBfill);

void encode(EncodeTiledFn fn, CUtensorMap* m, const void* ptr, uint32_t rows, uint32_t chunks) {
    cuuint64_t dims[4] = {64, (cuuint64_t)kS, 4, (cuuint64_t)kH};
    cuuint64_t strides[3] = {(cuuint64_t)kD * 2, 128, (cuuint64_t)kS * kD * 2};
    cuuint32_t box[4] = {64, rows, chunks, 1};
    cuuint32_t es[4] = {1, 1, 1, 1};
    fn(m, CU_TENSOR_MAP_DATA_TYPE_BFLOAT16, 4, const_cast<void*>(ptr), dims, strides, box, es,
       CU_TENSOR_MAP_INTERLEAVE_NONE, CU_TENSOR_MAP_SWIZZLE_128B, CU_TENSOR_MAP_L2_PROMOTION_NONE,
       CU_TENSOR_MAP_FLOAT_OOB_FILL_NONE);
}

}

extern "C" void kernel_launch(void* const* d_in, const int* in_sizes, int n_in, void* d_out, int out_size) {
    (void)in_sizes; (void)n_in; (void)out_size;
    const __nv_bfloat16* q = (const __nv_bfloat16*)d_in[0];
    const __nv_bfloat16* k = (const __nv_bfloat16*)d_in[1];
    const __nv_bfloat16* v = (const __nv_bfloat16*)d_in[2];
    const int* win = (const int*)d_in[3];
    const int* glob = (const int*)d_in[4];
    __nv_bfloat16* out = (__nv_bfloat16*)d_out;

    void* fn = nullptr;
    cudaDriverEntryPointQueryResult qr;
    cudaGetDriverEntryPoint("cuTensorMapEncodeTiled", &fn, cudaEnableDefault, &qr);
    EncodeTiledFn enc_fn = (EncodeTiledFn)fn;
    Maps maps;
    encode(enc_fn, &maps.q, q, 64, 1);
    encode(enc_fn, &maps.k, k, 64, 1);
    encode(enc_fn, &maps.v, v, 64, 1);
    encode(enc_fn, &maps.o, out, 16, 1);
    encode(enc_fn, &maps.kg, k, 8, 4);
    encode(enc_fn, &maps.vg, v, 8, 4);
    encode(enc_fn, &maps.qg, q, 8, 4);
    cudaFuncSetAttribute(attn_kernel, cudaFuncAttributeMaxDynamicSharedMemorySize, kSmemBytes);
    void* part = nullptr;
    cudaGetSymbolAddress(&part, g_part);
    attn_kernel<<<kH * 8, kThreads, kSmemBytes>>>(win, glob, (uint4*)part, out, q, k, v, maps TUNE_ARG);
}
```

```cpp
#include <cuda_runtime.h>
#include <cuda_bf16.h>
#include <cuda.h>
#include <stdint.h>

namespace {

constexpr int kS = 2048, kD = 256, kH = 16;
constexpr int kThreads = 384;
constexpr int kMaxWin = 32;
constexpr int kMaxGlob = 8;

constexpr uint32_t kSlotBytes = 32768, kPieceBytes = 8192;
constexpr uint32_t kOffK = 4 * kSlotBytes, kKStride = kSlotBytes + 4096;
constexpr uint32_t kOffVg = kOffK + 2 * kKStride;
constexpr uint32_t kOffQg = kOffVg + 4096;
constexpr uint32_t kOffPg = kOffQg + 4096;
constexpr uint32_t kOffBar = kOffPg + 5 * 1280;
constexpr uint32_t kBarFull = kOffBar;
constexpr uint32_t kBarG = kBarFull + 56 * 8;
constexpr uint32_t kBarEmpty = kBarG + 8;
constexpr uint32_t kBarP = kBarEmpty + 14 * 8;
constexpr uint32_t kSmemBytes = kBarP + 6 * 8;
constexpr unsigned long long kEmptyCounts = 0x11111111AA6995ull;
constexpr uint32_t base = 1024;
constexpr uint32_t kFullQ = base + kBarFull, kFullK = kFullQ + 4 * 32, kFullV = kFullQ + 9 * 32;

constexpr float kScaleLog2 = 0.0625f * 1.4426950408889634f;

struct Sched { uint32_t e[48]; };
struct Maps { CUtensorMap qr, kr, vr, qc, vc, orow, oc, kg, vg, qg; };

constexpr int kEarlyBlock = 2;
constexpr int kInbox = 8 * 4 * 2;
__device__ __align__(128) uint4 g_part[kH * 8 * kInbox];

__device__ __forceinline__ uint32_t smem_u32(const void* p) { return (uint32_t)__cvta_generic_to_shared(p); }
__device__ __forceinline__ void mbar_init(uint32_t b, uint32_t c) {
    asm volatile("mbarrier.init.shared::cta.b64 [%0], %1;" ::"r"(b), "r"(c) : "memory");
}
__device__ __forceinline__ void mbar_expect(uint32_t b, uint32_t bytes) {
    asm volatile("mbarrier.arrive.expect_tx.shared::cta.b64 _, [%0], %1;" ::"r"(b), "r"(bytes) : "memory");
}
__device__ __forceinline__ void mbar_arrive(uint32_t b) {
    asm volatile("mbarrier.arrive.shared::cta.b64 _, [%0];" ::"r"(b) : "memory");
}
__device__ __forceinline__ void mbar_wait(uint32_t b) {
    asm volatile(
        "{\n.reg .pred p, q;\n.reg .u32 n;\nmov.u32 n, 0;\n"
        "LW%=:\n"
        "mbarrier.try_wait.parity.shared::cta.b64 p, [%0], 0;\n"
        "@p bra LD%=;\n"
        "add.u32 n, n, 1;\n"
        "setp.lt.u32 q, n, 4000000;\n"
        "@q bra LW%=;\n"
        "LD%=:\n}\n" ::"r"(b) : "memory");
}
__device__ __forceinline__ int ld_param(const int* p) {
    int v;
    asm volatile("ld.global.nc.s32 %0, [%1];" : "=r"(v) : "l"(p));
    return v;
}
__device__ __forceinline__ uint32_t gtime_lo() {
    uint32_t t;
    asm volatile("mov.u32 %0, %globaltimer_lo;" : "=r"(t));
    return t;
}
__device__ __forceinline__ void mbar_wait_until(uint32_t b, uint32_t due) {
    asm volatile(
        "{\n.reg .pred p, q;\n.reg .u32 t;\n.reg .s32 d;\n"
        "LW%=:\n"
        "mbarrier.test_wait.parity.shared::cta.b64 p, [%0], 0;\n"
        "@p bra LD%=;\n"
        "mov.u32 t, %globaltimer_lo;\n"
        "sub.s32 d, t, %1;\n"
        "setp.lt.s32 q, d, 0;\n"
        "@q bra LW%=;\n"
        "LD%=:\n}\n" ::"r"(b), "r"(due) : "memory");
}
__device__ __forceinline__ void mbar_arrive_n(uint32_t b, uint32_t n) {
    asm volatile("mbarrier.arrive.shared::cta.b64 _, [%0], %1;" ::"r"(b), "r"(n) : "memory");
}
__device__ __forceinline__ bool elect_one() {
    uint32_t p;
    asm volatile("{\n.reg .pred p;\nelect.sync _|p, 0xffffffff;\nselp.u32 %0, 1, 0, p;\n}\n" : "=r"(p));
    return p;
}
__device__ __forceinline__ uint64_t policy_evict_first() {
    uint64_t pol;
    asm("createpolicy.fractional.L2::evict_first.b64 %0, 1.0;" : "=l"(pol));
    return pol;
}
__device__ __forceinline__ void tma_load(uint32_t dst, const CUtensorMap* m, uint32_t bar, int chunk, int group,
                                         int head, uint64_t pol) {
    asm volatile(
        "cp.async.bulk.tensor.5d.shared::cluster.global.mbarrier::complete_tx::bytes.L2::cache_hint "
        "[%0], [%1, {%3,%3,%4,%5,%6}], [%2], %7;" ::"r"(dst), "l"(m), "r"(bar), "r"(0), "r"(chunk), "r"(group),
        "r"(head), "l"(pol) : "memory");
}
__device__ __forceinline__ void tma_load_elect(uint32_t dst, const CUtensorMap* m, uint32_t bar, int chunk, int group,
                                               int head, uint64_t pol) {
    asm volatile(
        "{\n.reg .pred p;\nelect.sync _|p, 0xffffffff;\n"
        "@p mbarrier.arrive.expect_tx.shared::cta.b64 _, [%2], %8;\n"
        "@p cp.async.bulk.tensor.5d.shared::cluster.global.mbarrier::complete_tx::bytes.L2::cache_hint "
        "[%0], [%1, {%3,%3,%4,%5,%6}], [%2], %7;\n}\n" ::"r"(dst), "l"(m), "r"(bar), "r"(0), "r"(chunk), "r"(group),
        "r"(head), "l"(pol), "n"(kPieceBytes) : "memory");
}
__device__ __forceinline__ void tma_load_head(uint32_t dst, const CUtensorMap* m, uint32_t bar, int head) {
    asm volatile(
        "cp.async.bulk.tensor.5d.shared::cluster.global.mbarrier::complete_tx::bytes "
        "[%0], [%1, {%3,%3,%3,%3,%4}], [%2];" ::"r"(dst), "l"(m), "r"(bar), "r"(0), "r"(head) : "memory");
}
__device__ __forceinline__ void tma_store_elect(uint32_t src, const CUtensorMap* m, int chunk, int group, int head) {
    asm volatile(
        "{\n.reg .pred p;\nelect.sync _|p, 0xffffffff;\n"
        "@p cp.async.bulk.tensor.5d.global.shared::cta.bulk_group [%1, {%2,%2,%3,%4,%5}], [%0];\n}\n" ::"r"(src),
        "l"(m), "r"(0), "r"(chunk), "r"(group), "r"(head) : "memory");
}
__device__ __forceinline__ void mbar_wait4(uint32_t b) {
#pragma unroll
    for (int x = 0; x < 4; x++) mbar_wait(b + 8 * x);
}
__device__ __forceinline__ float ex2(float x) {
    float y;
    asm("ex2.approx.ftz.f32 %0, %1;" : "=f"(y) : "f"(x));
    return y;
}
__device__ __forceinline__ uint32_t pack_bf16(float lo, float hi) {
    uint32_t r;
    asm("cvt.rn.bf16x2.f32 %0, %1, %2;" : "=r"(r) : "f"(hi), "f"(lo));
    return r;
}
__device__ __forceinline__ uint32_t make_desc(uint32_t addr) { return ((addr & 0x3FFFF) >> 4) | (1u << 16); }
constexpr uint32_t kHiCol = (1024u >> 4) | (1u << 30), kHiRow = (4096u >> 4) | (1u << 30), kHi0 = 1u << 30;
__device__ __forceinline__ void wg_fence() { asm volatile("wgmma.fence.sync.aligned;" ::: "memory"); }
__device__ __forceinline__ void wg_commit() { asm volatile("wgmma.commit_group.sync.aligned;" ::: "memory"); }
template <int N>
__device__ __forceinline__ void wg_wait() { asm volatile("wgmma.wait_group.sync.aligned %0;" ::"n"(N) : "memory"); }

#define F4(a, i) "+f"(a[i]), "+f"(a[i + 1]), "+f"(a[i + 2]), "+f"(a[i + 3])
#define F16(a, i) F4(a, i), F4(a, i + 4), F4(a, i + 8), F4(a, i + 12)

#define O4(a, i) "=f"(a[i]), "=f"(a[i + 1]), "=f"(a[i + 2]), "=f"(a[i + 3])
#define O16(a, i) O4(a, i), O4(a, i + 4), O4(a, i + 8), O4(a, i + 12)
#define ACC32 "{%0,%1,%2,%3,%4,%5,%6,%7,%8,%9,%10,%11,%12,%13,%14,%15," \
              "%16,%17,%18,%19,%20,%21,%22,%23,%24,%25,%26,%27,%28,%29,%30,%31}, "

__device__ __forceinline__ void acc_ready(float (&d)[32]) { asm volatile("" : F16(d, 0), F16(d, 16)::"memory"); }

__device__ __forceinline__ void wgmma_ss_n64(float (&d)[32], uint32_t da, uint32_t ha, uint32_t db) {
    asm volatile(
        "{\n.reg .pred p;\n.reg .b64 a, b;\nsetp.eq.b32 p, 0, 0;\n"
        "mov.b64 a, {%32, %33};\nmov.b64 b, {%34, %35};\n"
        "wgmma.mma_async.sync.aligned.m64n64k16.f32.bf16.bf16 " ACC32 "a, b, p, 1, 1, 0, 0;\n}\n"
        : F16(d, 0), F16(d, 16) : "r"(da), "r"(ha), "r"(db), "n"(kHiRow));
}
__device__ __forceinline__ void wgmma_ss_n72(float (&d)[32], float (&g)[4], uint32_t da, uint32_t ha, uint32_t db) {
    asm volatile(
        "{\n.reg .pred p;\n.reg .b64 a, b;\nsetp.eq.b32 p, 0, 0;\n"
        "mov.b64 a, {%36, %37};\nmov.b64 b, {%38, %39};\n"
        "wgmma.mma_async.sync.aligned.m64n72k16.f32.bf16.bf16 "
        "{%0,%1,%2,%3,%4,%5,%6,%7,%8,%9,%10,%11,%12,%13,%14,%15,%16,%17,%18,%19,%20,%21,%22,%23,"
        "%24,%25,%26,%27,%28,%29,%30,%31,%32,%33,%34,%35}, a, b, p, 1, 1, 0, 0;\n}\n"
        : F16(d, 0), F16(d, 16), F4(g, 0) : "r"(da), "r"(ha), "r"(db), "n"(kHiRow));
}
template <uint32_t HI>
__device__ __forceinline__ void wgmma_rs_n64(float (&d)[32], uint32_t a0, uint32_t a1, uint32_t a2, uint32_t a3,
                                             uint32_t db) {
    asm volatile(
        "{\n.reg .pred p;\n.reg .b64 b;\nsetp.eq.b32 p, 0, 0;\n"
        "mov.b64 b, {%36, %37};\n"
        "wgmma.mma_async.sync.aligned.m64n64k16.f32.bf16.bf16 " ACC32 "{%32,%33,%34,%35}, b, p, 1, 1, 1;\n}\n"
        : F16(d, 0), F16(d, 16) : "r"(a0), "r"(a1), "r"(a2), "r"(a3), "r"(db), "n"(HI));
}
__device__ __forceinline__ void wgmma_rs_n64_init(float (&d)[32], uint32_t a0, uint32_t a1, uint32_t a2, uint32_t a3,
                                                  uint32_t db) {
    asm volatile(
        "{\n.reg .pred p;\n.reg .b64 b;\nsetp.ne.b32 p, 0, 0;\n"
        "mov.b64 b, {%36, %37};\n"
        "wgmma.mma_async.sync.aligned.m64n64k16.f32.bf16.bf16 " ACC32 "{%32,%33,%34,%35}, b, p, 1, 1, 1;\n}\n"
        : O16(d, 0), O16(d, 16) : "r"(a0), "r"(a1), "r"(a2), "r"(a3), "r"(db), "n"(kHi0));
}
__device__ __forceinline__ void mma_16816(float (&d)[4], uint32_t a0, uint32_t a1, uint32_t a2, uint32_t a3,
                                          uint32_t b0, uint32_t b1) {
    asm(
        "mma.sync.aligned.m16n8k16.row.col.f32.bf16.bf16.f32 {%0,%1,%2,%3}, {%4,%5,%6,%7}, {%8,%9}, {%0,%1,%2,%3};"
        : F4(d, 0) : "r"(a0), "r"(a1), "r"(a2), "r"(a3), "r"(b0), "r"(b1));
}
__device__ __forceinline__ void ldsm_x4(uint32_t (&r)[4], uint32_t addr) {
    asm volatile("ldmatrix.sync.aligned.m8n8.x4.shared.b16 {%0,%1,%2,%3}, [%4];"
                 : "=r"(r[0]), "=r"(r[1]), "=r"(r[2]), "=r"(r[3]) : "r"(addr) : "memory");
}
__device__ __forceinline__ void ldsm_x4_t(uint32_t (&r)[4], uint32_t addr) {
    asm volatile("ldmatrix.sync.aligned.m8n8.x4.trans.shared.b16 {%0,%1,%2,%3}, [%4];"
                 : "=r"(r[0]), "=r"(r[1]), "=r"(r[2]), "=r"(r[3]) : "r"(addr) : "memory");
}
__device__ __forceinline__ void stsm_x4(uint32_t addr, uint32_t r0, uint32_t r1, uint32_t r2, uint32_t r3) {
    asm volatile("stmatrix.sync.aligned.m8n8.x4.shared.b16 [%0], {%1,%2,%3,%4};" ::"r"(addr), "r"(r0), "r"(r1),
                 "r"(r2), "r"(r3) : "memory");
}
__device__ __forceinline__ void stsm_x4_t(uint32_t addr, uint32_t r0, uint32_t r1, uint32_t r2, uint32_t r3) {
    asm volatile("stmatrix.sync.aligned.m8n8.x4.trans.shared.b16 [%0], {%1,%2,%3,%4};" ::"r"(addr), "r"(r0), "r"(r1),
                 "r"(r2), "r"(r3) : "memory");
}
__device__ __forceinline__ void sts_v4(uint32_t addr, uint32_t a, uint32_t b, uint32_t c, uint32_t d) {
    asm volatile("st.shared.v4.u32 [%0], {%1,%2,%3,%4};" ::"r"(addr), "r"(a), "r"(b), "r"(c), "r"(d) : "memory");
}
__device__ __forceinline__ void sts_v2(uint32_t addr, uint32_t a, uint32_t b) {
    asm volatile("st.shared.v2.u32 [%0], {%1,%2};" ::"r"(addr), "r"(a), "r"(b) : "memory");
}
__device__ __forceinline__ float2 lds_f2(uint32_t addr) {
    float2 v;
    asm volatile("ld.shared.v2.f32 {%0,%1}, [%2];" : "=f"(v.x), "=f"(v.y) : "r"(addr) : "memory");
    return v;
}
__device__ __forceinline__ uint4 lds_v4(uint32_t addr) {
    uint4 v;
    asm volatile("ld.shared.v4.u32 {%0,%1,%2,%3}, [%4];" : "=r"(v.x), "=r"(v.y), "=r"(v.z), "=r"(v.w) : "r"(addr) : "memory");
    return v;
}
__device__ __forceinline__ uint32_t movm_t(uint32_t a) {
    uint32_t d;
    asm volatile("movmatrix.sync.aligned.m8n8.trans.b16 %0, %1;" : "=r"(d) : "r"(a));
    return d;
}
__device__ __forceinline__ uint4 enc_stats(float a, float b, float c, float d) {
    return make_uint4(__float_as_uint(a) | 1u, __float_as_uint(b) | 1u, __float_as_uint(c) | 1u,
                      __float_as_uint(d) | 1u);
}
__device__ __forceinline__ void st_part(uint4* p, const uint4& v, bool on) {
    asm volatile(
        "{\n.reg .pred p;\nsetp.ne.b32 p, %5, 0;\n"
        "@p st.relaxed.gpu.global.v4.u32 [%0], {%1,%2,%3,%4};\n}\n" ::"l"(p), "r"(v.x), "r"(v.y), "r"(v.z), "r"(v.w),
        "r"((int)on) : "memory");
}
__device__ __forceinline__ void red_bf16x8(__nv_bfloat16* p, const uint4& v, bool on) {
    asm volatile(
        "{\n.reg .pred p;\nsetp.ne.b32 p, %5, 0;\n"
        "@p red.relaxed.gpu.global.add.noftz.v4.bf16x2 [%0], {%1,%2,%3,%4};\n}\n" ::"l"(p), "r"(v.x), "r"(v.y),
        "r"(v.z), "r"(v.w), "r"((int)on) : "memory");
}
__device__ __forceinline__ float dec(uint32_t u) { return __uint_as_float(u); }
__device__ __forceinline__ uint4 ld_part(const uint4* p) {
    uint4 v;
    asm volatile("ld.relaxed.gpu.global.v4.u32 {%0,%1,%2,%3}, [%4];"
                 : "=r"(v.x), "=r"(v.y), "=r"(v.z), "=r"(v.w) : "l"(p) : "memory");
    return v;
}
__device__ __forceinline__ bool ready(const uint4& v) { return v.x && v.y && v.z && v.w; }

__device__ __forceinline__ void generic_rows(const __nv_bfloat16* q, const __nv_bfloat16* k, const __nv_bfloat16* v,
                                          __nv_bfloat16* out, int head, int r0, int W, int G) {
    const int warp = threadIdx.x >> 5, lane = threadIdx.x & 31;
    const size_t hb = (size_t)head * kS * kD;
#pragma unroll 1
    for (int i = r0 + warp; i < r0 + 256; i += 8) {
        float qf[8], o[8];
        {
            uint4 u = *reinterpret_cast<const uint4*>(q + hb + (size_t)i * kD + lane * 8);
            const __nv_bfloat16* e = reinterpret_cast<const __nv_bfloat16*>(&u);
#pragma unroll
            for (int x = 0; x < 8; x++) { qf[x] = __bfloat162float(e[x]); o[x] = 0.f; }
        }
        const bool none = (W < 0) && (G <= 0);
        float m = -INFINITY, l = 0.f;
#pragma unroll 1
        for (int j = 0; j < kS; j++) {
            const long long dist = (long long)i - j;
            const bool on = (dist <= W && dist >= -(long long)W) || i < G || j < G;
            if (!on && !none) continue;
            float s = -1.0e9f;
            if (on) {
                uint4 u = *reinterpret_cast<const uint4*>(k + hb + (size_t)j * kD + lane * 8);
                const __nv_bfloat16* e = reinterpret_cast<const __nv_bfloat16*>(&u);
                s = 0.f;
#pragma unroll
                for (int x = 0; x < 8; x++) s += qf[x] * __bfloat162float(e[x]);
#pragma unroll
                for (int x = 16; x; x >>= 1) s += __shfl_xor_sync(0xffffffffu, s, x);
                s *= 0.0625f;
            }
            const float mn = fmaxf(m, s);
            const float a = __expf(m - mn), p = __expf(s - mn);
            uint4 u = *reinterpret_cast<const uint4*>(v + hb + (size_t)j * kD + lane * 8);
            const __nv_bfloat16* e = reinterpret_cast<const __nv_bfloat16*>(&u);
#pragma unroll
            for (int x = 0; x < 8; x++) o[x] = o[x] * a + p * __bfloat162float(e[x]);
            l = l * a + p;
            m = mn;
        }
        const float inv = 1.f / l;
        uint4 r;
        r.x = pack_bf16(o[0] * inv, o[1] * inv);
        r.y = pack_bf16(o[2] * inv, o[3] * inv);
        r.z = pack_bf16(o[4] * inv, o[5] * inv);
        r.w = pack_bf16(o[6] * inv, o[7] * inv);
        *reinterpret_cast<uint4*>(out + hb + (size_t)i * kD + lane * 8) = r;
    }
}

__device__ __forceinline__ void stage_chunk(uint32_t dst, const float (&o)[32], float r0, float r1) {
#pragma unroll
    for (int x = 0; x < 4; x++)
        stsm_x4(dst ^ (x << 5), pack_bf16(o[8 * x] * r0, o[8 * x + 1] * r0),
                pack_bf16(o[8 * x + 2] * r1, o[8 * x + 3] * r1), pack_bf16(o[8 * x + 4] * r0, o[8 * x + 5] * r0),
                pack_bf16(o[8 * x + 6] * r1, o[8 * x + 7] * r1));
}
__device__ __forceinline__ void store_chunk(uint32_t stage, const CUtensorMap* mo, int row, int c, int head,
                                            const float (&o)[32], float r0, float r1, int lane) {
    stage_chunk(stage + (lane & 15) * 128 + (((lane >> 4) ^ (lane & 7)) << 4), o, r0, r1);
    asm volatile("fence.proxy.async.shared::cta;" ::: "memory");
    __syncwarp();
    tma_store_elect(stage, mo, c, row >> 3, head);
}

__device__ __forceinline__ void mask_init(float (&s)[32], int i0, int cq, int W, int G) {
    const int lo0 = max(i0 - W, G) - cq, hi0 = min(i0 + W, kS - 1) - cq;
    const int lo1 = max(i0 + 8 - W, G) - cq, hi1 = min(i0 + 8 + W, kS - 1) - cq;
#pragma unroll
    for (int x = 0; x < 16; x++) {
        const int c = 8 * (x >> 1) + (x & 1), i = 4 * (x >> 1) + (x & 1);
        s[i] = (c >= lo0 && c <= hi0) ? 0.f : -INFINITY;
        s[i + 2] = (c >= lo1 && c <= hi1) ? 0.f : -INFINITY;
    }
}

struct Merge {
    uint32_t in_a[16];
    float pick[8], drop[8];
};
template <int R>
__device__ __forceinline__ float row_max(float (&sa)[32], const float (&sb)[32], const float (&sg)[4], const Merge& mg,
                                         float& d) {
    float m0 = sg[2 * R], m1 = sg[2 * R + 1];
    d = -INFINITY;
#pragma unroll
    for (int x = 0; x < 16; x++) {
        const int n = x >> 1, e = x & 1, i = 4 * n + 2 * R + e;
        if ((n & 1) == R) {
            d = fmaxf(d, sb[i] + mg.pick[(n & ~1) + e]);
            sa[i] = fmaxf(sa[i], sb[i] + mg.drop[(n & ~1) + e]);
        } else {
            sa[i] = fmaxf(sa[i], sb[i]);
        }
        if (e) m1 = fmaxf(m1, sa[i]); else m0 = fmaxf(m0, sa[i]);
    }
    m0 = fmaxf(fmaxf(m0, m1), d);
    m0 = fmaxf(m0, __shfl_xor_sync(0xffffffffu, m0, 1));
    return fmaxf(m0, __shfl_xor_sync(0xffffffffu, m0, 2));
}
template <int R>
__device__ __forceinline__ float row_exp(const float (&sa)[32], const float (&sg)[4], const Merge& mg, float d, float mx,
                                         int warp, int lane, uint32_t (&pa)[16], uint32_t (&pb)[16], uint32_t& pg) {
    const float b = -mx * kScaleLog2;
    float l0 = ex2(fmaf(sg[2 * R], kScaleLog2, b)), l1 = ex2(fmaf(sg[2 * R + 1], kScaleLog2, b));
    pg = pack_bf16(l0, l1);
    const float pd = ex2(fmaf(d, kScaleLog2, b));
    const uint32_t dp = pack_bf16(pd, 0.f) << (4 * (lane & 4));
    l0 += pd;
#pragma unroll
    for (int n = 0; n < 8; n++) {
        const int i = 4 * n + 2 * R;
        const float p0 = ex2(fmaf(sa[i], kScaleLog2, b)), p1 = ex2(fmaf(sa[i + 1], kScaleLog2, b));
        l0 += p0;
        l1 += p1;
        const uint32_t pk = pack_bf16(p0, p1);
        pa[2 * n + R] = pk & mg.in_a[2 * n + R];
        pb[2 * n + R] = pk & ~mg.in_a[2 * n + R];
        if ((n & 1) == R) pb[2 * n + R] |= warp == (n >> 1) ? dp : 0u;
    }
    return l0 + l1;
}
__device__ __forceinline__ void pv_issue(float (&o)[32], const uint32_t (&p)[16], uint32_t dv) {
#pragma unroll
    for (int kk = 0; kk < 4; kk++)
        wgmma_rs_n64<kHiCol>(o, p[4 * kk], p[4 * kk + 1], p[4 * kk + 2], p[4 * kk + 3], dv + ((kk * 2048) >> 4));
}
__device__ __forceinline__ void pv_chunk(float (&o)[32], const uint32_t (&p)[16], uint32_t bar, uint32_t dv) {
    mbar_wait(bar);
    wg_fence();
    pv_issue(o, p, dv);
}

__device__ __forceinline__ void row_scale(float l0, float l1, bool zero0, float& r0, float& r1) {
    l0 += __shfl_xor_sync(0xffffffffu, l0, 1);
    l1 += __shfl_xor_sync(0xffffffffu, l1, 1);
    l0 += __shfl_xor_sync(0xffffffffu, l0, 2);
    l1 += __shfl_xor_sync(0xffffffffu, l1, 2);
    r0 = zero0 ? 0.f : __fdividef(1.f, l0);
    r1 = __fdividef(1.f, l1);
}

__device__ __forceinline__ void local_tile(int t, int qrow, int rk, int dr, int W, int G, int warp, int lane,
                                           const Maps& maps, int head) {
    const uint32_t sQ = base + (uint32_t)(t & 1) * kSlotBytes;
    const uint32_t fQ = kFullQ + 32 * t, fK = kFullK + 32 * t, fV = kFullV + 32 * t;
    const int row = qrow + warp * 16, g0 = 2 * (lane & 3), i0 = row + (lane >> 2);
    const bool bwd = dr < 0;
    float sa[32], sb[32], sg[4];
    mask_init(sa, i0, rk + dr * t + g0, W, G);
    mask_init(sb, i0, rk + dr * (t + 1) + g0, W, G);
    sg[0] = sg[2] = g0 < G ? 0.f : -INFINITY;
    sg[1] = sg[3] = g0 + 1 < G ? 0.f : -INFINITY;
    Merge mg;
#pragma unroll
    for (int x = 0; x < 16; x++) {
        const int i = 4 * (x >> 1) + 2 * (x & 1);
        mg.in_a[x] = ~__byte_perm(__float_as_uint(sa[i]), __float_as_uint(sa[i + 1]), 0x7733);
    }
#pragma unroll
    for (int x = 0; x < 8; x++) {
        const bool hit = warp == (x >> 1) && (lane & 3) == (lane >> 3) && (x & 1) == ((lane >> 2) & 1);
        mg.pick[x] = hit ? 0.f : -INFINITY;
        mg.drop[x] = hit ? -INFINITY : 0.f;
    }
    acc_ready(sa);
    {
        const uint32_t dKa = make_desc(base + kOffK + (t & 1) * kKStride);
        const uint32_t dKb = make_desc(base + kOffK + (~t & 1) * kKStride);
        const uint32_t hQ = t == 3 ? kHiCol : kHiRow;
        mbar_wait4(fK);
        mbar_wait4(t == 3 ? fK + 32 : fQ);
#pragma unroll 1
        for (int st = 0; st < 4; st++) {
            const int c = bwd ? 3 - st : st;
            const uint32_t dQ = make_desc(sQ) + c * (t == 3 ? 512 : 64);
            if (t == 3) mbar_wait(fQ + 8 * st);
            wg_fence();
#pragma unroll
            for (int x = 0; x < 4; x++) wgmma_ss_n72(sa, sg, dQ + 2 * x, hQ, dKa + c * 64 + 2 * x);
            wg_commit();
            if (t == 3) {
                wg_fence();
#pragma unroll
                for (int x = 0; x < 4; x++) wgmma_ss_n64(sb, dQ + 2 * x, kHiCol, dKb + c * 64 + 2 * x);
                wg_commit();
            }
        }
        if (t == 3) {
            mbar_wait(fV);
            wg_wait<0>();
        } else {
            wg_wait<0>();
            if (lane == 0) mbar_arrive(base + kBarEmpty + 8 * t);
            mbar_wait4(fK + 32);
            wg_fence();
#pragma unroll
            for (int x = 0; x < 16; x++) {
                const uint32_t off = (x >> 2) * 64 + 2 * (x & 3);
                wgmma_ss_n64(sb, make_desc(sQ) + off, kHiRow, dKb + off);
            }
            wg_commit();
            if (t) mbar_wait4(fV);
            wg_wait<0>();
            if (t < 2 && lane == 0) mbar_arrive(base + kBarEmpty + 8 * (t + 1));
        }
    }
    uint32_t pa[16], pb[16], pg0, pg1;
    acc_ready(sa);
    acc_ready(sb);
    asm volatile("" : F4(sg, 0)::"memory");
    float d0, d1;
    const float mx0 = row_max<0>(sa, sb, sg, mg, d0);
    const float mx1 = row_max<1>(sa, sb, sg, mg, d1);
    const float l0 = row_exp<0>(sa, sg, mg, d0, mx0, warp, lane, pa, pb, pg0);
    const float l1 = row_exp<1>(sa, sg, mg, d1, mx1, warp, lane, pa, pb, pg1);

    float o[4][32];
    const uint32_t dVa = make_desc(base + (uint32_t)(2 + (t & 1)) * kSlotBytes);
    const uint32_t dVb = make_desc(base + (uint32_t)(3 - (t & 1)) * kSlotBytes);
    const uint32_t dVg = make_desc(base + kOffVg);
    uint32_t z0, z1;
    asm volatile("shr.u32 %0, %2, 8;\nshr.u32 %1, %3, 8;" : "=r"(z0), "=r"(z1) : "r"(G), "r"(W));
    float r0, r1;
    wg_fence();
#pragma unroll
    for (int c = 0; c < 4; c++) wgmma_rs_n64_init(o[c], pg0, pg1, z0, z1, dVg + ((c * 1024) >> 4));
    wg_commit();
    if (t < 3) {
        if (t == 0) mbar_wait4(fV);
        wg_fence();
#pragma unroll
        for (int x = 0; x < 16; x++) {
            const int kk = x >> 2, c = x & 3;
            wgmma_rs_n64<kHiRow>(o[c], pa[4 * kk], pa[4 * kk + 1], pa[4 * kk + 2], pa[4 * kk + 3],
                                 dVa + ((kk * 8192 + c * 1024) >> 4));
        }
        wg_commit();
    } else {
        wg_fence();
        pv_issue(o[0], pa, dVa);
        wg_commit();
        pv_chunk(o[1], pa, fV + 8, dVa + (8192 >> 4));
        wg_commit();
    }
    row_scale(l0, l1, i0 < G, r0, r1);
    if (t < 3) {
        wg_wait<0>();
        if (lane == 0) mbar_arrive(base + kBarEmpty + 8 * (3 + t));
    }
    if (t < 2) {
        wg_wait<0>();
        const uint32_t stage = sQ + warp * 8192;
#pragma unroll
        for (int x = 0; x < 8; x++) {
            const uint32_t u = pb[x], w = pb[x ^ 12];
            pb[x] = bwd ? w : u;
            pb[x ^ 12] = bwd ? u : w;
        }
        const int mine = bwd ? 3 - warp : warp;
#pragma unroll 1
        for (int i = 0; i < 5; i++) {
            if (i < 4) {
                mbar_wait(fV + 32 + 8 * i);
                wg_fence();
#pragma unroll
                for (int c = 0; c < 4; c++)
                    wgmma_rs_n64<kHiRow>(o[c], pb[0], pb[1], pb[2], pb[3],
                                         dVb + (bwd ? 3 - i : i) * 512 + ((c * 1024) >> 4));
                wg_commit();
                wg_wait<0>();
                if (i == 3 && lane == 0) mbar_arrive(base + kBarEmpty + 8 * (4 + t));
#pragma unroll
                for (int x = 0; x < 12; x++) pb[x] = pb[x + 4];
            }
            if (i == mine) {
                const uint32_t dst =
                    stage + ((lane >> 3) & 1) * 4096 + (lane & 7) * 128 + (((lane >> 4) ^ (lane & 7)) << 4);
#pragma unroll
                for (int c = 0; c < 4; c++) stage_chunk(dst + c * 1024, o[c], r0, r1);
                asm volatile("fence.proxy.async.shared::cta;" ::: "memory");
                __syncwarp();
                tma_store_elect(stage, &maps.orow, 0, row >> 3, head);
            }
            if (i == mine + 1) {
                asm volatile("cp.async.bulk.commit_group;\ncp.async.bulk.wait_group 0;" ::: "memory");
                __syncwarp();
                if (lane == 0) mbar_arrive(base + kBarEmpty + 8 * (6 + 4 * t + mine));
            }
        }
    } else {
        const uint32_t stage = sQ + warp * (t == 3 ? 2048 : 8192), step = t == 3 ? 8192 : 2048;
#pragma unroll
        for (int c = 0; c < 4; c++) {
            if (c >= 2 && t == 3) {
                pv_chunk(o[c], pa, fV + 8 * c, dVa + ((c * 8192) >> 4));
                wg_commit();
            }
            pv_chunk(o[c], pb, fV + 32 + 8 * c, dVb + ((c * 8192) >> 4));
            wg_commit();
            wg_wait<0>();
            store_chunk(stage + c * step, &maps.oc, row, c, head, o[c], r0, r1, lane);
        }
    }
}

__global__ void __launch_bounds__(kThreads, 1)
attn_kernel(const int* __restrict__ p_win, const int* __restrict__ p_glob, uint4* __restrict__ part,
            __nv_bfloat16* __restrict__ out, const __nv_bfloat16* __restrict__ q,
            const __nv_bfloat16* __restrict__ k, const __nv_bfloat16* __restrict__ v,
            const __grid_constant__ Sched sched, const __grid_constant__ Maps maps) {
    extern __shared__ uint8_t smem_raw[];
    const int warp = __shfl_sync(0xffffffffu, threadIdx.x >> 5, 0), lane = threadIdx.x & 31;
    const int head = blockIdx.x >> 3, chunk = blockIdx.x & 7;
    const int r0 = chunk * 256;
    const bool bwd = chunk & 1;
    const int rq = bwd ? r0 + 192 : r0, rk = bwd ? r0 + 224 : r0 - 32, dr = bwd ? -64 : 64;

    const bool leader = elect_one();
    if (warp < 8 && leader) {
        const uint32_t fb = (warp < 4 ? kFullK : kFullQ) + 8 * (warp & 3);
        mbar_init(fb, 1);
        mbar_expect(fb, kPieceBytes);
        tma_load(base + (warp < 4 ? kOffK : 0) + (warp & 3) * kPieceBytes, warp < 4 ? &maps.kr : &maps.qr, fb,
                 0, ((warp < 4 ? rk : rq) >> 3) + 2 * (warp & 3), head, policy_evict_first());
    }
    const uint32_t t_start = gtime_lo() - 64;
    if (smem_u32(smem_raw) != base) __trap();
    int W, G;
    if (warp != 10) {
        W = ld_param(p_win);
        G = ld_param(p_glob);
    } else {
        W = (int)sched.e[lane];
        G = (int)sched.e[32 + (lane & 15)];
    }
    if (leader) {
        if (warp == 11) {
            mbar_init(base + kBarG, 1);
#pragma unroll
            for (int b = 0; b < 14; b++) mbar_init(base + kBarEmpty + 8 * b, (uint32_t)(kEmptyCounts >> (4 * b)) & 15);
#pragma unroll
            for (int b = 0; b < 6; b++) mbar_init(base + kBarP + 8 * b, 1);
            mbar_expect(base + kBarG, 4 * 4096);
            tma_load_head(base + kOffK + kSlotBytes, &maps.kg, base + kBarG, head);
            tma_load_head(base + kOffK + kKStride + kSlotBytes, &maps.kg, base + kBarG, head);
            tma_load_head(base + kOffQg, &maps.qg, base + kBarG, head);
            tma_load_head(base + kOffVg, &maps.vg, base + kBarG, head);
        } else if (warp == 8) {
#pragma unroll
            for (int b = 4; b < 32; b++)
                if (b < 16 || b >= 20) mbar_init(kFullQ + 8 * b, 1);
        } else if (warp == 9) {
#pragma unroll
            for (int b = 32; b < 56; b++) mbar_init(kFullQ + 8 * b, 1);
        }
    }
    asm volatile("fence.mbarrier_init.release.cluster;" ::: "memory");
    __syncthreads();

    if (warp < 8) {
        asm volatile("setmaxnreg.inc.sync.aligned.u32 200;");
        W = __shfl_sync(0xffffffffu, W, 0);
        G = __shfl_sync(0xffffffffu, G, 0);
        if (W < 0 || W > kMaxWin || G < 0 || G > kMaxGlob) {
            generic_rows(q, k, v, out, head, r0, W, G);
            return;
        }
        const int wq = warp & 3;
        mbar_wait(base + kBarG);
#pragma unroll 1
        for (int t = warp >> 2; t < 4; t += 2)
            local_tile(t, rq + dr * t, rk, dr, W, G, wq, lane, maps, head);
        asm volatile("cp.async.bulk.commit_group;\ncp.async.bulk.wait_group.read 0;" ::: "memory");
    } else {
        asm volatile("setmaxnreg.dec.sync.aligned.u32 104;");
        if (warp == 10) {
            const uint64_t pol = policy_evict_first();
            uint32_t dt[2];
            int gr[2];
#pragma unroll
            for (int h = 0; h < 2; h++) {
                const uint32_t e = (uint32_t)(h ? G : W);
                const int blk = (e >> 2) & 15;
                const int ty = blk < 4 ? 0 : blk < 9 ? 1 : 2, idx = blk - (ty == 0 ? 0 : ty == 1 ? 4 : 9);
                const bool cols = ty != 1 && idx >= 3;
                const int pos = (bwd && (ty == 0 || blk == 10 || blk == 11)) ? 3 - (e & 3) : e & 3;
                const uint32_t off = ty == 1 ? kOffK + (idx & 1) * kKStride : (ty + (idx & 1)) * kSlotBytes;
                dt[h] = (base + off + pos * kPieceBytes) | (cols ? pos : 0) << 18 |
                        (cols ? 3 + (ty >> 1) : ty) << 20;
                gr[h] = (((ty ? rk : rq) + dr * idx) >> 3) + (cols ? 0 : 2 * pos);
            }
#pragma unroll 1
            for (int i = 0; i < 48; i++) {
                const uint32_t e = (uint32_t)__shfl_sync(0xffffffffu, i < 32 ? W : G, i & 31);
                const uint32_t d = __shfl_sync(0xffffffffu, i < 32 ? dt[0] : dt[1], i & 31);
                int grp = __shfl_sync(0xffffffffu, i < 32 ? gr[0] : gr[1], i & 31);
                uint32_t dst = d & 0x3FFFF, fb = kFullQ + 8 * (e & 63), col = (d >> 18) & 3;
                const CUtensorMap* map = &maps.qr + (d >> 20);
                asm volatile("" : "+r"(dst), "+r"(fb), "+r"(col), "+r"(grp), "+l"(map));
                const uint32_t wp = (e >> 6) & 63, ew = (e >> 12) & 15;
                if (ew != 15) mbar_wait(base + kBarEmpty + 8 * ew);
                if (e >> 16) mbar_wait_until(kFullQ + 8 * wp, t_start + (e >> 16));
                tma_load_elect(dst, map, fb, col, grp, head, pol);
            }
            return;
        }
        W = __shfl_sync(0xffffffffu, W, 0);
        G = __shfl_sync(0xffffffffu, G, 0);
        if (W < 0 || W > kMaxWin || G < 0 || G > kMaxGlob) {
            if (warp == 8) {
                if (lane < 14) mbar_arrive_n(base + kBarEmpty + 8 * lane, (uint32_t)(kEmptyCounts >> (4 * lane)) & 15);
#pragma unroll 1
                for (int x = 0; x < 57; x++) mbar_wait(kFullQ + 8 * x);
            }
            return;
        }
        const uint32_t edge0 = bwd ? 0 : 16384;
        const bool pub = 2 * (lane & 3) < G;
        if (warp == 11) {
            float m0 = -INFINITY, m1 = -INFINITY, l0 = 0.f, l1 = 0.f;
            const uint32_t aQ = base + kOffQg + (lane & 7) * 128 + (((lane >> 3) ^ (lane & 7)) << 4);
            const uint32_t lK =
                base + kOffK + ((lane >> 3) & 1) * 4096 + (lane & 7) * 128 + (((lane >> 4) ^ (lane & 7)) << 4);
            const bool late = (lane >> 2) & 1;
            uint4* const rml =
                part + (head * 8 + (lane >> 3)) * kInbox + (chunk * 4 + (lane & 3)) * 2 + ((lane >> 2) & 1);
            mbar_wait(base + kBarG);
            uint32_t qb[8][4];
#pragma unroll
            for (int x = 0; x < 8; x++) ldsm_x4(qb[x], (aQ ^ ((x & 1) << 6)) + (x >> 1) * 1024);
#pragma unroll 1
            for (int j = 0; j < 5; j++) {
                const bool full = j != 0 && j != 4;
                float s[4][4];
#pragma unroll
                for (int x = 0; x < 4; x++) s[0][x] = s[1][x] = -INFINITY;
#pragma unroll 1
                for (int h = full ? 1 : 0; h >= 0; h--) {
                    const int half = full ? 1 - h : ((j == 0) != bwd);
                    const uint32_t aK = lK + (j & 1) * kKStride + half * 16384;
                    float u[4][4];
#pragma unroll
                    for (int x = 0; x < 4; x++) {
                        s[2][x] = s[0][x];
                        s[3][x] = s[1][x];
                        u[0][x] = u[1][x] = u[2][x] = u[3][x] = 0.f;
                    }
                    mbar_wait(kFullK + 32 * j + 16 * half);
                    mbar_wait(kFullK + 32 * j + 16 * half + 8);
#pragma unroll
                    for (int c = 0; c < 4; c++) {
                        uint32_t f[8][4];
#pragma unroll
                        for (int x = 0; x < 8; x++) ldsm_x4(f[x], (aK ^ ((x >> 1) << 5)) + c * 1024 + (x & 1) * 8192);
#pragma unroll
                        for (int x = 0; x < 8; x++) {
                            const int kk = x >> 1;
                            mma_16816(u[x & 3], f[x][0], f[x][1], f[x][2], f[x][3], qb[2 * c + (kk >> 1)][2 * (kk & 1)],
                                      qb[2 * c + (kk >> 1)][2 * (kk & 1) + 1]);
                        }
                    }
#pragma unroll
                    for (int x = 0; x < 4; x++) {
                        s[0][x] = u[0][x] + u[2][x];
                        s[1][x] = u[1][x] + u[3][x];
                    }
                }
                __syncwarp();
                if (j < 3 && lane == 0) mbar_arrive(base + kBarEmpty + 8 * j);
                float mx0 = m0, mx1 = m1;
#pragma unroll
                for (int i = 0; i < 4; i++) {
                    mx0 = fmaxf(mx0, fmaxf(s[i][0], s[i][2]));
                    mx1 = fmaxf(mx1, fmaxf(s[i][1], s[i][3]));
                }
#pragma unroll
                for (int x = 4; x < 32; x <<= 1) {
                    mx0 = fmaxf(mx0, __shfl_xor_sync(0xffffffffu, mx0, x));
                    mx1 = fmaxf(mx1, __shfl_xor_sync(0xffffffffu, mx1, x));
                }
                const float b0 = mx0 == -INFINITY ? 0.f : -mx0 * kScaleLog2;
                const float b1 = mx1 == -INFINITY ? 0.f : -mx1 * kScaleLog2;
                const float a0 = ex2(fmaf(m0, kScaleLog2, b0)), a1 = ex2(fmaf(m1, kScaleLog2, b1));
                m0 = mx0;
                m1 = mx1;
                l0 *= a0;
                l1 *= a1;
                uint32_t pf[8];
#pragma unroll
                for (int i = 0; i < 4; i++) {
                    const float p0 = ex2(fmaf(s[i][0], kScaleLog2, b0)), p1 = ex2(fmaf(s[i][1], kScaleLog2, b1));
                    const float p2 = ex2(fmaf(s[i][2], kScaleLog2, b0)), p3 = ex2(fmaf(s[i][3], kScaleLog2, b1));
                    l0 += p0 + p2;
                    l1 += p1 + p3;
                    pf[2 * i] = movm_t(pack_bf16(p0, p1));
                    pf[2 * i + 1] = movm_t(pack_bf16(p2, p3));
                }
                const uint32_t aP = base + kOffPg + j * 1280;
                sts_v4(aP + (full ? 512 : 0) + lane * 16, pf[0], pf[1], pf[2], pf[3]);
                sts_v4(aP + (full ? 0 : 512) + lane * 16, pf[4], pf[5], pf[6], pf[7]);
                sts_v2(aP + 1024 + lane * 8, __float_as_uint(a0), __float_as_uint(a1));
                __syncwarp();
                if (lane == 0) mbar_arrive(base + kBarP + 8 * j);
                if (j == kEarlyBlock || j == 4) {
#pragma unroll
                    for (int x = 4; x < 32; x <<= 1) {
                        l0 += __shfl_xor_sync(0xffffffffu, l0, x);
                        l1 += __shfl_xor_sync(0xffffffffu, l1, x);
                    }
                    const uint4 rec = (late && j != 4) ? make_uint4(0, 0, 0, 0) : enc_stats(m0, m1, l0, l1);
                    st_part(rml, rec, pub && (late || j != 4));
                    st_part(rml + 4 * kInbox, rec, pub && (late || j != 4));
                    l0 = l1 = 0.f;
                }
            }
            uint4* const in = part + (head * 8 + chunk) * kInbox + lane * 2;
            uint4 me = make_uint4(1, 1, 1, 1), ml = me;
            int it = 0;
            do {
                if (pub) {
                    me = ld_part(in);
                    ml = ld_part(in + 1);
                }
            } while (!__all_sync(0xffffffffu, ready(me) && ready(ml)) && ++it < 2000000);
            float M0 = dec(ml.x), M1 = dec(ml.y);
#pragma unroll
            for (int x = 4; x < 32; x <<= 1) {
                M0 = fmaxf(M0, __shfl_xor_sync(0xffffffffu, M0, x));
                M1 = fmaxf(M1, __shfl_xor_sync(0xffffffffu, M1, x));
            }
            float L0 = ex2((dec(me.x) - M0) * kScaleLog2) * dec(me.z) + ex2((dec(ml.x) - M0) * kScaleLog2) * dec(ml.z);
            float L1 = ex2((dec(me.y) - M1) * kScaleLog2) * dec(me.w) + ex2((dec(ml.y) - M1) * kScaleLog2) * dec(ml.w);
#pragma unroll
            for (int x = 4; x < 32; x <<= 1) {
                L0 += __shfl_xor_sync(0xffffffffu, L0, x);
                L1 += __shfl_xor_sync(0xffffffffu, L1, x);
            }
            const float f0 = __fdividef(ex2((m0 - M0) * kScaleLog2), L0);
            const float f1 = __fdividef(ex2((m1 - M1) * kScaleLog2), L1);
            sts_v2(base + kOffPg + 4 * 1280 + 512 + lane * 8, __float_as_uint(f0), __float_as_uint(f1));
            __syncwarp();
            if (lane == 0) mbar_arrive(base + kBarP + 8 * 5);
            st_part(in, make_uint4(0, 0, 0, 0), pub);
            st_part(in + 1, make_uint4(0, 0, 0, 0), pub);
        } else {
            const int g = warp - 8;
            if (g == 0) {
                mbar_wait(base + kBarG);
                if (lane < 5) asm volatile("prefetch.tensormap [%0];" ::"l"(&maps.vr + lane) : "memory");
                __syncwarp();
            }
            float og[4][2][4];
#pragma unroll
            for (int i = 0; i < 8; i++) og[i >> 1][i & 1][0] = og[i >> 1][i & 1][1] = og[i >> 1][i & 1][2] = og[i >> 1][i & 1][3] = 0.f;
            const uint32_t lV = base + (lane & 7) * 128 + (((4 * g + ((lane >> 3) & 1)) ^ (lane & 7)) << 4);
            const uint32_t aP = base + kOffPg + lane * 16, aA = base + kOffPg + 1024 + lane * 8;
#pragma unroll 1
            for (int j = 0; j < 3; j++) {
                const uint32_t aV = lV + (lane >> 4) * 4096 + (uint32_t)(2 + (j & 1)) * kSlotBytes + (j ? 0 : edge0);
                const uint32_t aV2 = aV + (j ? 16384 : 0);
                mbar_wait(base + kBarP + 8 * j);
                const uint4 p0 = lds_v4(aP + j * 1280), p1 = lds_v4(aP + j * 1280 + 512);
                const float2 al = lds_f2(aA + j * 1280);
                const float a0 = al.x, a1 = al.y;
#pragma unroll
                for (int i = 0; i < 8; i++) {
                    float(&t)[4] = og[i >> 1][i & 1];
                    t[0] *= a0; t[1] *= a1; t[2] *= a0; t[3] *= a1;
                }
                mbar_wait4(kFullV + 32 * j);
#pragma unroll
                for (int c = 0; c < 4; c++) {
                    uint32_t f[8][4];
#pragma unroll
                    for (int x = 0; x < 8; x++)
                        ldsm_x4_t(f[x], ((x < 4 ? aV : aV2) ^ ((x & 1) << 5)) + c * 1024 + ((x >> 1) & 1) * 8192);
#pragma unroll
                    for (int x = 0; x < 8; x++) {
                        const int kk = x >> 1;
                        mma_16816(og[c][x & 1], f[x][0], f[x][1], f[x][2], f[x][3],
                                  kk == 0 ? p0.x : kk == 1 ? p0.z : kk == 2 ? p1.x : p1.z,
                                  kk == 0 ? p0.y : kk == 1 ? p0.w : kk == 2 ? p1.y : p1.w);
                    }
                }
                __syncwarp();
                if (lane == 0) mbar_arrive(base + kBarEmpty + 8 * (3 + j));
            }
            {
                const uint32_t aV = lV + (lane >> 4) * 1024 + 3 * kSlotBytes;
                const uint32_t aV4 = lV + (lane >> 4) * 1024 + 2 * kSlotBytes + (bwd ? 4096 : 0);
                const uint32_t fV = kFullV + 32 * 3;
                mbar_wait(base + kBarP + 8 * 4);
                const uint4 p0 = lds_v4(aP + 3 * 1280), p1 = lds_v4(aP + 3 * 1280 + 512), p4 = lds_v4(aP + 4 * 1280);
                const float2 al = lds_f2(aA + 3 * 1280), a4 = lds_f2(aA + 4 * 1280);
#pragma unroll
                for (int i = 0; i < 8; i++) {
                    float(&t)[4] = og[i >> 1][i & 1];
                    t[0] *= al.x; t[1] *= al.y; t[2] *= al.x; t[3] *= al.y;
                }
                const uint32_t aT = base + kOffQg + g * 2048;
                __nv_bfloat16* const op = out + ((size_t)head * kS + (lane >> 2)) * kD + g * 32 + 8 * (lane & 3);
                const bool red_on = (lane >> 2) < G;
                float f0 = 0.f, f1 = 0.f;
#pragma unroll
                for (int c = 0; c < 4; c++) {
                    if (c == 3) {
                        mbar_wait(base + kBarP + 8 * 5);
                        const float2 fs = lds_f2(aA + 4 * 1280 - 512);
                        f0 = fs.x;
                        f1 = fs.y;
#pragma unroll
                        for (int y = 0; y < 3; y++)
                            stsm_x4_t(aT + y * 512 + (lane & 7) * 64 + (lane >> 3) * 16,
                                      pack_bf16(og[y][0][0] * f0, og[y][0][1] * f1), pack_bf16(og[y][0][2] * f0, og[y][0][3] * f1),
                                      pack_bf16(og[y][1][0] * f0, og[y][1][1] * f1), pack_bf16(og[y][1][2] * f0, og[y][1][3] * f1));
                        __syncwarp();
#pragma unroll
                        for (int y = 0; y < 3; y++) red_bf16x8(op + y * 64, lds_v4(aT + y * 512 + lane * 16), red_on);
                        __syncwarp();
                    }
                    float tm[2][4];
#pragma unroll
                    for (int x = 0; x < 2; x++) tm[x][0] = tm[x][1] = tm[x][2] = tm[x][3] = 0.f;
                    mbar_wait(fV + 8 * c);
                    uint32_t f[8][4];
#pragma unroll
                    for (int x = 0; x < 8; x++) ldsm_x4_t(f[x], (aV ^ ((x & 1) << 5)) + c * 8192 + (x >> 1) * 2048);
#pragma unroll
                    for (int x = 0; x < 4; x++) {
                        mma_16816(og[c][x & 1], f[x][0], f[x][1], f[x][2], f[x][3], x < 2 ? p0.x : p0.z,
                                  x < 2 ? p0.y : p0.w);
                        mma_16816(tm[x & 1], f[x + 4][0], f[x + 4][1], f[x + 4][2], f[x + 4][3], x < 2 ? p1.x : p1.z,
                                  x < 2 ? p1.y : p1.w);
                    }
#pragma unroll
                    for (int x = 0; x < 2; x++) {
#pragma unroll
                        for (int y = 0; y < 4; y++) {
                            og[c][x][y] = (og[c][x][y] + tm[x][y]) * ((y & 1) ? a4.y : a4.x);
                            tm[x][y] = 0.f;
                        }
                    }
                    mbar_wait(fV + 32 + 8 * c);
#pragma unroll
                    for (int x = 0; x < 4; x++) ldsm_x4_t(f[x], (aV4 ^ ((x & 1) << 5)) + c * 8192 + (x >> 1) * 2048);
#pragma unroll
                    for (int x = 0; x < 2; x++) {
                        mma_16816(og[c][x], f[x][0], f[x][1], f[x][2], f[x][3], p4.x, p4.y);
                        mma_16816(tm[x], f[x + 2][0], f[x + 2][1], f[x + 2][2], f[x + 2][3], p4.z, p4.w);
                    }
#pragma unroll
                    for (int x = 0; x < 2; x++)
#pragma unroll
                        for (int y = 0; y < 4; y++) og[c][x][y] += tm[x][y];
                }
                stsm_x4_t(aT + (lane & 7) * 64 + (lane >> 3) * 16, pack_bf16(og[3][0][0] * f0, og[3][0][1] * f1),
                          pack_bf16(og[3][0][2] * f0, og[3][0][3] * f1), pack_bf16(og[3][1][0] * f0, og[3][1][1] * f1),
                          pack_bf16(og[3][1][2] * f0, og[3][1][3] * f1));
                __syncwarp();
                red_bf16x8(op + 3 * 64, lds_v4(aT + lane * 16), red_on);
            }
        }
    }
}

typedef CUresult (*EncodeTiledFn)(CUtensorMap*, CUtensorMapDataType, cuuint32_t, void*, const cuuint64_t*,
                                  const cuuint64_t*, const cuuint32_t*, const cuuint32_t*, CUtensorMapInterleave,
                                  CUtensorMapSwizzle, CUtensorMapL2promotion, CUtensorMapFloatOOBfill);

void encode(EncodeTiledFn fn, CUtensorMap* m, const void* ptr, uint32_t chunks, uint32_t groups) {
    cuuint64_t dims[5] = {64, 8, 4, (cuuint64_t)kS / 8, (cuuint64_t)kH};
    cuuint64_t strides[4] = {(cuuint64_t)kD * 2, 128, (cuuint64_t)kD * 2 * 8, (cuuint64_t)kS * kD * 2};
    cuuint32_t box[5] = {64, 8, chunks, groups, 1};
    cuuint32_t es[5] = {1, 1, 1, 1, 1};
    fn(m, CU_TENSOR_MAP_DATA_TYPE_BFLOAT16, 5, const_cast<void*>(ptr), dims, strides, box, es,
       CU_TENSOR_MAP_INTERLEAVE_NONE, CU_TENSOR_MAP_SWIZZLE_128B, CU_TENSOR_MAP_L2_PROMOTION_NONE,
       CU_TENSOR_MAP_FLOAT_OOB_FILL_NONE);
}

const char kOrder[] =
    "K00K01K02K03Q00Q01Q02Q03K10K11K12K13V00V01V02V03"
    "V10V11Q10Q11Q12Q13V12K20K21V13K22K23"
    "V20V21Q20Q21Q22Q23V22K30K31V23K32K33"
    "V30K40K41K42K43Q30Q31Q32Q33V31V40V41V32V42V33V43";
constexpr int kWindow = 4;
constexpr int kFreePieces = 12;
constexpr int kPace = 342;
constexpr int kPace0 = -715;
constexpr int kTailFrom = 48, kTailPace = 400;

Sched make_sched() {
    Sched sc;
    int id[56];
    int t2 = 2 * kPace0;
    bool seen[14] = {};
    for (int i = 0; i < 56; i++) {
        const char ty = kOrder[3 * i];
        const int idx = kOrder[3 * i + 1] - '0', piece = kOrder[3 * i + 2] - '0';
        const int blk = (ty == 'Q' ? 0 : ty == 'K' ? 4 : 9) + idx;
        id[i] = blk * 4 + piece;
        int rel = 15;
        if (idx >= 2) {
            if (ty == 'Q') rel = 6 + 4 * (idx - 2) + piece;
            else if (!seen[blk]) rel = (ty == 'K' ? 0 : 3) + idx - 2;
        }
        seen[blk] = true;
        const int due = i < kFreePieces ? 0 : t2 / 2;
        if (i >= 8)
            sc.e[i - 8] = (uint32_t)id[i] | (uint32_t)id[i - kWindow] << 6 | (uint32_t)rel << 12 | (uint32_t)due << 16;
        t2 += ((ty != 'Q' && (idx == 0 || idx == 4)) ? 1 : 2) * (i >= kTailFrom ? kTailPace : kPace);
    }
    return sc;
}

}

extern "C" void kernel_launch(void* const* d_in, const int* in_sizes, int n_in, void* d_out, int out_size) {
    (void)in_sizes; (void)n_in; (void)out_size;
    const __nv_bfloat16* q = (const __nv_bfloat16*)d_in[0];
    const __nv_bfloat16* k = (const __nv_bfloat16*)d_in[1];
    const __nv_bfloat16* v = (const __nv_bfloat16*)d_in[2];
    const int* win = (const int*)d_in[3];
    const int* glob = (const int*)d_in[4];
    __nv_bfloat16* out = (__nv_bfloat16*)d_out;

    void* fn = nullptr;
    cudaDriverEntryPointQueryResult qr;
    cudaGetDriverEntryPoint("cuTensorMapEncodeTiled", &fn, cudaEnableDefault, &qr);
    EncodeTiledFn enc_fn = (EncodeTiledFn)fn;
    Maps maps;
    encode(enc_fn, &maps.qr, q, 4, 2);
    encode(enc_fn, &maps.kr, k, 4, 2);
    encode(enc_fn, &maps.vr, v, 4, 2);
    encode(enc_fn, &maps.qc, q, 1, 8);
    encode(enc_fn, &maps.vc, v, 1, 8);
    encode(enc_fn, &maps.orow, out, 4, 2);
    encode(enc_fn, &maps.oc, out, 1, 2);
    encode(enc_fn, &maps.kg, k, 4, 1);
    encode(enc_fn, &maps.vg, v, 4, 1);
    encode(enc_fn, &maps.qg, q, 4, 1);
    cudaFuncSetAttribute(attn_kernel, cudaFuncAttributeMaxDynamicSharedMemorySize, kSmemBytes);
    void* part = nullptr;
    cudaGetSymbolAddress(&part, g_part);
    attn_kernel<<<kH * 8, kThreads, kSmemBytes>>>(win, glob, (uint4*)part, out, q, k, v, make_sched(), maps);
}
```
